```python
import torch

def _softmax(x, axis=-1):
    return torch.softmax(x, dim=axis)
def _gelu(x):
    return torch.nn.functional.gelu(x, approximate="tanh")
def _silu(x):
    return torch.nn.functional.silu(x)
def _sigmoid(x):
    return torch.sigmoid(x)
def _layernorm(x, axis=-1, eps=1e-5):
    m = x.mean(dim=axis, keepdim=True)
    v = x.var(dim=axis, keepdim=True, unbiased=False)
    return (x - m) / torch.sqrt(v + eps)
def _scatter_add(tgt, idx, src, axis=0):
    return tgt.clone().index_add_(axis, idx, src)
def _segment_sum(src, seg, n):
    out = torch.zeros((n,) + src.shape[1:], dtype=src.dtype)
    return out.index_add_(0, seg, src)
def _pad(x, pw):
    flat = tuple(v for pair in reversed(pw) for v in pair)
    return torch.nn.functional.pad(x, flat)

kernel_name = 'interleave_layers__linear_kernel_hedgehog__glu_gated_glu__prompt'

def setup_inputs():

    _w = (lambda a: (lambda t: t.to(torch.bfloat16) if t.is_floating_point() else t)(torch.as_tensor(a)))
    def _A_setup():
        B, S, D, H = 1, 2048, 448, 16
        Dh = D // H
        return {
            "x": _w((lambda *s: torch.randn(*s, dtype=torch.bfloat16) * 0.05)(B, S, D)),
            "wqkv": _w((lambda *s: torch.randn(*s, dtype=torch.bfloat16) * 0.4)(D, 3 * D)),
            "w_phi": _w((lambda *s: torch.randn(*s, dtype=torch.bfloat16) * 0.4)(H, Dh, Dh) * (Dh ** -0.5)),
            "wo": _w((lambda *s: torch.randn(*s, dtype=torch.bfloat16) * 0.05)(D, D)),
        }
    _A_in = _A_setup()

    def _B_setup():
        B, S, D, F = 1, 2048, 448, 1792
        return {
            "x": _w((lambda *s: torch.randn(*s, dtype=torch.bfloat16) * 0.05)(B, S, D)),
            "w_gate": _w((lambda *s: torch.randn(*s, dtype=torch.bfloat16) * 0.05)(D, F)),
            "w_up": _w((lambda *s: torch.randn(*s, dtype=torch.bfloat16) * 0.05)(D, F)),
            "w_down": _w((lambda *s: torch.randn(*s, dtype=torch.bfloat16) * 0.05)(F, D)),
        }
    _B_in = _B_setup()

    return {
        "A_x": _A_in["x"],
        "A_wqkv": _A_in["wqkv"],
        "A_w_phi": _A_in["w_phi"],
        "A_wo": _A_in["wo"],
        "B_x": _B_in["x"],
        "B_w_gate": _B_in["w_gate"],
        "B_w_up": _B_in["w_up"],
        "B_w_down": _B_in["w_down"],
    }

def reference(A_x, A_wqkv, A_w_phi, A_wo, B_x, B_w_gate, B_w_up, B_w_down):
    def _A_ref(x, wqkv, w_phi, wo):
        B, S, D = x.shape
        H = 16; Dh = D // H
        qkv = (lambda x, *d: x.permute(*d))((x @ wqkv).reshape(B, S, 3, H, Dh), 2, 0, 3, 1, 4)
        q, k, v = qkv[0], qkv[1], qkv[2]
        pq = torch.einsum("bhsd,hdf->bhsf", q, w_phi)
        pk = torch.einsum("bhsd,hdf->bhsf", k, w_phi)
        phi_q = torch.concatenate([_softmax(pq, axis=-1), _softmax(-pq, axis=-1)], axis=-1)
        phi_k = torch.concatenate([_softmax(pk, axis=-1), _softmax(-pk, axis=-1)], axis=-1)
        kv = torch.einsum("bhsf,bhsd->bhfd", phi_k, v)
        z  = torch.einsum("bhsf->bhf", phi_k)
        num = torch.einsum("bhqf,bhfd->bhqd", phi_q, kv)
        den = torch.einsum("bhqf,bhf->bhq", phi_q, z)[..., None] + 1e-6
        o = num / den
        return (lambda x, *d: x.permute(*d))(o, 0, 2, 1, 3).reshape(B, S, D) @ wo

    def _B_ref(x, w_gate, w_up, w_down):
        g = torch.einsum("bsd,df->bsf", x, w_gate)
        u = torch.einsum("bsd,df->bsf", x, w_up)
        h = _sigmoid(g) * u
        return torch.einsum("bsf,fd->bsd", h, w_down)

    x = A_x
    x = x + _A_ref(_layernorm(x, axis=-1), A_wqkv, A_w_phi, A_wo)
    x = x + _B_ref(_layernorm(x, axis=-1), B_w_gate, B_w_up, B_w_down)
    x = x + _A_ref(_layernorm(x, axis=-1), A_wqkv, A_w_phi, A_wo)
    x = x + _B_ref(_layernorm(x, axis=-1), B_w_gate, B_w_up, B_w_down)
    return x
```

```cpp
#include <cuda_runtime.h>
#include <cuda_bf16.h>
#include <cuda_fp16.h>
#include <cuda.h>
#include <stdint.h>

#define SOFF 229376
#define DO 300
#define DX1 0
#define DX2 0
#define QD 2100
#define PFD 500
#define DK1 200
#define WISH 0
#define PROFILE 0

struct __align__(128) Half { uint8_t b[7680]; };
namespace {

struct Desc {
  uint64_t z; uint32_t o;
  __device__ __forceinline__ Desc operator+(uint32_t k) const { return Desc{z, o + k}; }
};
__device__ __forceinline__ void wgmma_mo_n8_a(float (&d)[4], Desc da, uint64_t db) {
  asm volatile("{\n.reg .b64 dsc;\nadd.s64 dsc, %4, %5;\n"
    "wgmma.mma_async.sync.aligned.m64n8k16.f32.bf16.bf16 {%0, %1, %2, %3}, dsc, %6, 1, 1, 1, 1, 0;\n}\n"
    : "+f"(d[0]), "+f"(d[1]), "+f"(d[2]), "+f"(d[3])
    : "l"(da.z), "l"(da.o + 0ull), "l"(db));
}
__device__ __forceinline__ void wgmma_mo_n8_i(float (&d)[4], Desc da, uint64_t db) {
  asm volatile("{\n.reg .b64 dsc;\nadd.s64 dsc, %4, %5;\n"
    "wgmma.mma_async.sync.aligned.m64n8k16.f32.bf16.bf16 {%0, %1, %2, %3}, dsc, %6, 0, 1, 1, 1, 0;\n}\n"
    : "=f"(d[0]), "=f"(d[1]), "=f"(d[2]), "=f"(d[3])
    : "l"(da.z), "l"(da.o + 0ull), "l"(db));
}
__device__ __forceinline__ void wgmma_mo_n8(float (&d)[4], Desc da, uint64_t db, bool acc) {
  if (acc) wgmma_mo_n8_a(d, da, db); else wgmma_mo_n8_i(d, da, db);
}
__device__ __forceinline__ void wgmma_rs_n56_a(float (&d)[28], uint32_t a0, uint32_t a1, uint32_t a2, uint32_t a3, Desc db) {
  asm volatile("{\n.reg .b64 dsc;\nadd.s64 dsc, %32, %33;\n"
    "wgmma.mma_async.sync.aligned.m64n56k16.f32.bf16.bf16 {%0, %1, %2, %3, %4, %5, %6, %7, %8, %9, %10, %11, %12, %13, %14, %15, %16, %17, %18, %19, %20, %21, %22, %23, %24, %25, %26, %27}, {%28, %29, %30, %31}, dsc, 1, 1, 1, 1;\n}\n"
    : "+f"(d[0]), "+f"(d[1]), "+f"(d[2]), "+f"(d[3]), "+f"(d[4]), "+f"(d[5]), "+f"(d[6]), "+f"(d[7]), "+f"(d[8]), "+f"(d[9]), "+f"(d[10]), "+f"(d[11]), "+f"(d[12]), "+f"(d[13]), "+f"(d[14]), "+f"(d[15]), "+f"(d[16]), "+f"(d[17]), "+f"(d[18]), "+f"(d[19]), "+f"(d[20]), "+f"(d[21]), "+f"(d[22]), "+f"(d[23]), "+f"(d[24]), "+f"(d[25]), "+f"(d[26]), "+f"(d[27])
    : "r"(a0), "r"(a1), "r"(a2), "r"(a3), "l"(db.z), "l"(db.o + 0ull));
}
__device__ __forceinline__ void wgmma_rs_n56_i(float (&d)[28], uint32_t a0, uint32_t a1, uint32_t a2, uint32_t a3, Desc db) {
  asm volatile("{\n.reg .b64 dsc;\nadd.s64 dsc, %32, %33;\n"
    "wgmma.mma_async.sync.aligned.m64n56k16.f32.bf16.bf16 {%0, %1, %2, %3, %4, %5, %6, %7, %8, %9, %10, %11, %12, %13, %14, %15, %16, %17, %18, %19, %20, %21, %22, %23, %24, %25, %26, %27}, {%28, %29, %30, %31}, dsc, 0, 1, 1, 1;\n}\n"
    : "=f"(d[0]), "=f"(d[1]), "=f"(d[2]), "=f"(d[3]), "=f"(d[4]), "=f"(d[5]), "=f"(d[6]), "=f"(d[7]), "=f"(d[8]), "=f"(d[9]), "=f"(d[10]), "=f"(d[11]), "=f"(d[12]), "=f"(d[13]), "=f"(d[14]), "=f"(d[15]), "=f"(d[16]), "=f"(d[17]), "=f"(d[18]), "=f"(d[19]), "=f"(d[20]), "=f"(d[21]), "=f"(d[22]), "=f"(d[23]), "=f"(d[24]), "=f"(d[25]), "=f"(d[26]), "=f"(d[27])
    : "r"(a0), "r"(a1), "r"(a2), "r"(a3), "l"(db.z), "l"(db.o + 0ull));
}
__device__ __forceinline__ void wgmma_rs_n56_w(float (&d)[28], uint32_t a0, uint32_t a1, uint32_t a2, uint32_t a3, Desc db) {
  asm volatile("{\n.reg .b64 dsc;\nmov.b64 dsc, {%32, 0x400001C0};\n"
    "wgmma.mma_async.sync.aligned.m64n56k16.f32.bf16.bf16 {%0, %1, %2, %3, %4, %5, %6, %7, %8, %9, %10, %11, %12, %13, %14, %15, %16, %17, %18, %19, %20, %21, %22, %23, %24, %25, %26, %27}, {%28, %29, %30, %31}, dsc, 1, 1, 1, 1;\n}\n"
    : "+f"(d[0]), "+f"(d[1]), "+f"(d[2]), "+f"(d[3]), "+f"(d[4]), "+f"(d[5]), "+f"(d[6]), "+f"(d[7]), "+f"(d[8]), "+f"(d[9]), "+f"(d[10]), "+f"(d[11]), "+f"(d[12]), "+f"(d[13]), "+f"(d[14]), "+f"(d[15]), "+f"(d[16]), "+f"(d[17]), "+f"(d[18]), "+f"(d[19]), "+f"(d[20]), "+f"(d[21]), "+f"(d[22]), "+f"(d[23]), "+f"(d[24]), "+f"(d[25]), "+f"(d[26]), "+f"(d[27])
    : "r"(a0), "r"(a1), "r"(a2), "r"(a3), "r"((uint32_t)db.z + db.o));
}
__device__ __forceinline__ void wgmma_rs_n56(float (&d)[28], uint32_t a0, uint32_t a1, uint32_t a2, uint32_t a3, Desc db, bool acc) {
  if (acc) wgmma_rs_n56_a(d, a0, a1, a2, a3, db); else wgmma_rs_n56_i(d, a0, a1, a2, a3, db);
}
__device__ __forceinline__ void wgmma_sk_n64_a(float (&d)[32], Desc da, Desc db) {
  asm volatile("{\n.reg .b64 dsc, dsc2;\nadd.s64 dsc, %32, %33;\nadd.s64 dsc2, %34, %35;\n"
    "wgmma.mma_async.sync.aligned.m64n64k16.f32.bf16.bf16 {%0, %1, %2, %3, %4, %5, %6, %7, %8, %9, %10, %11, %12, %13, %14, %15, %16, %17, %18, %19, %20, %21, %22, %23, %24, %25, %26, %27, %28, %29, %30, %31}, dsc, dsc2, 1, 1, 1, 0, 1;\n}\n"
    : "+f"(d[0]), "+f"(d[1]), "+f"(d[2]), "+f"(d[3]), "+f"(d[4]), "+f"(d[5]), "+f"(d[6]), "+f"(d[7]), "+f"(d[8]), "+f"(d[9]), "+f"(d[10]), "+f"(d[11]), "+f"(d[12]), "+f"(d[13]), "+f"(d[14]), "+f"(d[15]), "+f"(d[16]), "+f"(d[17]), "+f"(d[18]), "+f"(d[19]), "+f"(d[20]), "+f"(d[21]), "+f"(d[22]), "+f"(d[23]), "+f"(d[24]), "+f"(d[25]), "+f"(d[26]), "+f"(d[27]), "+f"(d[28]), "+f"(d[29]), "+f"(d[30]), "+f"(d[31])
    : "l"(da.z), "l"(da.o + 0ull), "l"(db.z), "l"(db.o + 0ull));
}
__device__ __forceinline__ void wgmma_sk_n64_i(float (&d)[32], Desc da, Desc db) {
  asm volatile("{\n.reg .b64 dsc, dsc2;\nadd.s64 dsc, %32, %33;\nadd.s64 dsc2, %34, %35;\n"
    "wgmma.mma_async.sync.aligned.m64n64k16.f32.bf16.bf16 {%0, %1, %2, %3, %4, %5, %6, %7, %8, %9, %10, %11, %12, %13, %14, %15, %16, %17, %18, %19, %20, %21, %22, %23, %24, %25, %26, %27, %28, %29, %30, %31}, dsc, dsc2, 0, 1, 1, 0, 1;\n}\n"
    : "=f"(d[0]), "=f"(d[1]), "=f"(d[2]), "=f"(d[3]), "=f"(d[4]), "=f"(d[5]), "=f"(d[6]), "=f"(d[7]), "=f"(d[8]), "=f"(d[9]), "=f"(d[10]), "=f"(d[11]), "=f"(d[12]), "=f"(d[13]), "=f"(d[14]), "=f"(d[15]), "=f"(d[16]), "=f"(d[17]), "=f"(d[18]), "=f"(d[19]), "=f"(d[20]), "=f"(d[21]), "=f"(d[22]), "=f"(d[23]), "=f"(d[24]), "=f"(d[25]), "=f"(d[26]), "=f"(d[27]), "=f"(d[28]), "=f"(d[29]), "=f"(d[30]), "=f"(d[31])
    : "l"(da.z), "l"(da.o + 0ull), "l"(db.z), "l"(db.o + 0ull));
}
__device__ __forceinline__ void wgmma_sk_n64(float (&d)[32], Desc da, Desc db, bool acc) {
  if (acc) wgmma_sk_n64_a(d, da, db); else wgmma_sk_n64_i(d, da, db);
}
__device__ __forceinline__ void wgmma_ss_n64_a(float (&d)[32], Desc da, Desc db) {
  asm volatile("{\n.reg .b64 dsc, dsc2;\nadd.s64 dsc, %32, %33;\nadd.s64 dsc2, %34, %35;\n"
    "wgmma.mma_async.sync.aligned.m64n64k16.f32.bf16.bf16 {%0, %1, %2, %3, %4, %5, %6, %7, %8, %9, %10, %11, %12, %13, %14, %15, %16, %17, %18, %19, %20, %21, %22, %23, %24, %25, %26, %27, %28, %29, %30, %31}, dsc, dsc2, 1, 1, 1, 1, 1;\n}\n"
    : "+f"(d[0]), "+f"(d[1]), "+f"(d[2]), "+f"(d[3]), "+f"(d[4]), "+f"(d[5]), "+f"(d[6]), "+f"(d[7]), "+f"(d[8]), "+f"(d[9]), "+f"(d[10]), "+f"(d[11]), "+f"(d[12]), "+f"(d[13]), "+f"(d[14]), "+f"(d[15]), "+f"(d[16]), "+f"(d[17]), "+f"(d[18]), "+f"(d[19]), "+f"(d[20]), "+f"(d[21]), "+f"(d[22]), "+f"(d[23]), "+f"(d[24]), "+f"(d[25]), "+f"(d[26]), "+f"(d[27]), "+f"(d[28]), "+f"(d[29]), "+f"(d[30]), "+f"(d[31])
    : "l"(da.z), "l"(da.o + 0ull), "l"(db.z), "l"(db.o + 0ull));
}
__device__ __forceinline__ void wgmma_ss_n64_i(float (&d)[32], Desc da, Desc db) {
  asm volatile("{\n.reg .b64 dsc, dsc2;\nadd.s64 dsc, %32, %33;\nadd.s64 dsc2, %34, %35;\n"
    "wgmma.mma_async.sync.aligned.m64n64k16.f32.bf16.bf16 {%0, %1, %2, %3, %4, %5, %6, %7, %8, %9, %10, %11, %12, %13, %14, %15, %16, %17, %18, %19, %20, %21, %22, %23, %24, %25, %26, %27, %28, %29, %30, %31}, dsc, dsc2, 0, 1, 1, 1, 1;\n}\n"
    : "=f"(d[0]), "=f"(d[1]), "=f"(d[2]), "=f"(d[3]), "=f"(d[4]), "=f"(d[5]), "=f"(d[6]), "=f"(d[7]), "=f"(d[8]), "=f"(d[9]), "=f"(d[10]), "=f"(d[11]), "=f"(d[12]), "=f"(d[13]), "=f"(d[14]), "=f"(d[15]), "=f"(d[16]), "=f"(d[17]), "=f"(d[18]), "=f"(d[19]), "=f"(d[20]), "=f"(d[21]), "=f"(d[22]), "=f"(d[23]), "=f"(d[24]), "=f"(d[25]), "=f"(d[26]), "=f"(d[27]), "=f"(d[28]), "=f"(d[29]), "=f"(d[30]), "=f"(d[31])
    : "l"(da.z), "l"(da.o + 0ull), "l"(db.z), "l"(db.o + 0ull));
}
__device__ __forceinline__ void wgmma_ss_n64(float (&d)[32], Desc da, Desc db, bool acc) {
  if (acc) wgmma_ss_n64_a(d, da, db); else wgmma_ss_n64_i(d, da, db);
}

constexpr int kStages = 4;
constexpr uint32_t kStageBytes = 28672;
constexpr uint32_t kBoxBytes = 14336;
constexpr uint32_t kUnit = 7168, kSlot = 7680;
constexpr uint32_t OFF_L = kStages * kStageBytes;
constexpr uint32_t kLBytes = 54272;
constexpr uint32_t OFF_WP = OFF_L + 2 * kLBytes;
constexpr uint32_t OFF_BAR = OFF_WP + 8192;
constexpr uint32_t OFF_X6 = 3 * kStageBytes;
constexpr uint32_t OFF_ONES = OFF_L + kLBytes + 7 * kSlot;
constexpr uint32_t OFF_CSK = OFF_ONES + 192;
constexpr uint32_t OFF_KVS = OFF_L + kLBytes;
constexpr uint32_t OFF_E = OFF_L + 24576;
constexpr uint32_t OFF_CS = OFF_BAR + 208;
constexpr uint32_t OFF_TS = OFF_CS + 448;
constexpr uint32_t SMEM_BYTES = OFF_TS + (PROFILE ? 368 : 0);
constexpr uint32_t BAR_FULL = OFF_BAR, BAR_EMPTY = OFF_BAR + 48, BAR_XF = OFF_BAR + 96, BAR_LFREE = OFF_BAR + 160,
                   BAR_WP = OFF_BAR + 176, BAR_XIN = OFF_BAR + 184, BAR_RL = OFF_BAR + 192, BAR_RD = OFF_BAR + 200, BAR_KV = OFF_ONES + 128, BAR_CS = BAR_KV + 16,
                   OFF_RL = BAR_KV + 32;
#define KSPIN (1 << 20)
constexpr int kSpin = KSPIN;

struct __align__(128) Grp {
  Half ag[2][8];
  Half hx[8][4];
  Half pb[8][4];
};
struct __align__(128) Flg {
  uint32_t fl[3][32];
  uint32_t fh[8][32];
};
struct Pair {
  Grp g[2];
  uint8_t pre[128];
  Flg f[2];
  uint8_t pad[(2 << 20) - 2 * sizeof(Grp) - 2 * sizeof(Flg) - 128];
};
struct Scratch {
  uint4 kv1[8][16][16][32];
  uint4 kv2[8][128][4];
  uint8_t pre[32 * sizeof(Flg)];
  uint32_t claim[64];
  uint32_t epoch;
  uint8_t pad[(2 << 20) - (1 << 20) - 65536 - 32 * sizeof(Flg) - 260];
  Pair pr[16];
};
static_assert(sizeof(Scratch) == 17 << 21, "");
constexpr size_t kWd = (sizeof(Scratch) + (3 << 20)) >> 21 << 21;
__device__ uint8_t g_scratch[kWd + (2 << 21)];
#define TF(i) do {} while (0)
#define TS(i) do {} while (0)
#define TSV(i) do {} while (0)
#define TSG(i) do {} while (0)

__device__ __forceinline__ void mbar_init(uint32_t a, int c) { asm volatile("mbarrier.init.shared::cta.b64 [%0], %1;" ::"r"(a), "r"(c)); }
__device__ __forceinline__ bool elect() {
  uint32_t r;
  asm volatile("{\n.reg .pred p;\nelect.sync _|p, -1;\nselp.u32 %0, 1, 0, p;\n}" : "=r"(r));
  return r;
}
__device__ __forceinline__ void mbar_expect(uint32_t a, uint32_t b) { asm volatile("mbarrier.arrive.expect_tx.shared::cta.b64 _, [%0], %1;" ::"r"(a), "r"(b) : "memory"); }
__device__ __forceinline__ void mbar_arrive(uint32_t a) { asm volatile("mbarrier.arrive.shared::cta.b64 _, [%0];" ::"r"(a) : "memory"); }
__device__ __forceinline__ void mbar_wait(uint32_t a, uint32_t ph) {
  asm volatile(
      "{\n.reg .pred p, q;\n.reg .b32 n;\nmov.b32 n, 0;\n"
      "LW:\nmbarrier.try_wait.parity.shared::cta.b64 p, [%0], %1;\n@p bra LD;\n"
      "add.u32 n, n, 1;\nsetp.lt.u32 q, n, %2;\n@q bra LW;\ntrap;\nLD:\n}" ::"r"(a), "r"(ph), "n"(kSpin) : "memory");
}
__device__ __forceinline__ void mbar_wait_c(uint32_t a, uint32_t ph) {
  asm volatile(
      "{\n.reg .pred p;\nLW:\nmbarrier.try_wait.parity.shared::cta.b64 p, [%0], %1;\n"
      "add.s32 spin, spin, -1;\nsetp.gt.and.s32 p, spin, 0, !p;\n@p bra LW;\n}" ::"r"(a), "r"(ph) : "memory");
}
__device__ __forceinline__ void mbar_wait2(uint32_t a, uint32_t ph) {
  asm volatile(
      "{\n.reg .pred p, q;\nLW:\nmbarrier.try_wait.parity.shared::cta.b64 p, [%0], %1;\nmbarrier.try_wait.parity.shared::cta.b64 q, [%0+8], %1;\n"
      "add.s32 spin, spin, -1;\nand.pred p, p, q;\nsetp.gt.and.s32 p, spin, 0, !p;\n@p bra LW;\n}" ::"r"(a), "r"(ph) : "memory");
}
__device__ __forceinline__ void tma2d_e(uint32_t dst, const CUtensorMap* m, int c0, int c1, uint32_t bar) {
  asm volatile("{\n.reg .pred p;\nelect.sync _|p, -1;\n@p cp.async.bulk.tensor.2d.shared::cluster.global.mbarrier::complete_tx::bytes [%0], [%1, {%3,%4}], [%2];\n}" ::"r"(dst), "l"(m), "r"(bar), "r"(c0), "r"(c1) : "memory");
}
__device__ __forceinline__ void tma2d_mce(uint32_t dst, const CUtensorMap* m, int c0, int c1, uint32_t bar) {
  asm volatile("{\n.reg .pred p;\nelect.sync _|p, -1;\n@p cp.async.bulk.tensor.2d.shared::cluster.global.mbarrier::complete_tx::bytes.multicast::cluster [%0], [%1, {%3,%4}], [%2], %5;\n}" ::"r"(dst), "l"(m), "r"(bar), "r"(c0), "r"(c1), "h"((uint16_t)3) : "memory");
}
__device__ __forceinline__ void tma2d_mc(uint32_t dst, const CUtensorMap* m, int c0, int c1, uint32_t bar) {
  asm volatile("cp.async.bulk.tensor.2d.shared::cluster.global.mbarrier::complete_tx::bytes.multicast::cluster [%0], [%1, {%3,%4}], [%2], %5;" ::"r"(dst), "l"(m), "r"(bar), "r"(c0), "r"(c1), "h"((uint16_t)3) : "memory");
}
__device__ __forceinline__ void bulk_g2s(uint32_t dst, const void* src, uint32_t bytes, uint32_t bar) {
  asm volatile("cp.async.bulk.shared::cluster.global.mbarrier::complete_tx::bytes [%0], [%1], %2, [%3];" ::"r"(dst), "l"(src), "r"(bytes), "r"(bar) : "memory");
}
__device__ __forceinline__ void mbar_arrive_cl(uint32_t a) { asm volatile("mbarrier.arrive.shared::cluster.b64 _, [%0];" ::"r"(a) : "memory"); }
__device__ __forceinline__ uint32_t mapa(uint32_t a, uint32_t rank) {
  uint32_t r;
  asm("mapa.shared::cluster.u32 %0, %1, %2;" : "=r"(r) : "r"(a), "r"(rank));
  return r;
}
__device__ __forceinline__ void prefetch_l2(const void* p, uint32_t bytes) {
  asm volatile("cp.async.bulk.prefetch.L2.global [%0], %1;" ::"l"(p), "r"(bytes) : "memory");
}
__device__ __forceinline__ uint32_t ld32(const uint32_t* p) {
  uint32_t v;
  asm volatile("ld.relaxed.gpu.global.u32 %0, [%1];" : "=r"(v) : "l"(p) : "memory");
  return v;
}
__device__ __forceinline__ void st32(uint32_t* p, uint32_t v) { asm volatile("st.relaxed.gpu.global.u32 [%0], %1;" ::"l"(p), "r"(v) : "memory"); }
#define mkdesc(off) Desc{dz, (1024 + (off)) >> 4}
struct Dz { uint64_t z[8]; };
#define WG_FENCE asm volatile("wgmma.fence.sync.aligned;" ::: "memory")
#define WG_COMMIT asm volatile("wgmma.commit_group.sync.aligned;" ::: "memory")
#define WG_WAIT(n) asm volatile("wgmma.wait_group.sync.aligned %0;" ::"n"(n) : "memory")
#define FENCE_ASYNC asm volatile("fence.proxy.async.shared::cta;" ::: "memory")
#define SCHED_FENCE() asm volatile("{\n.reg .pred p;\n.reg .b32 t;\nLF:\nmov.u32 t, %%clock;\nsetp.eq.u32 p, t, %0;\n@p bra LF;\n}" ::"n"(0x5a5a5a5a) : "memory")
#define TAKE(id, who) asm volatile("{\n.reg .pred p;\nsetp.ne.u32 p, %0, 0;\n@p bar.sync " #id ", 256;\n}" ::"r"((uint32_t)(who)) : "memory")
#define GIVE(id, who) asm volatile("{\n.reg .pred p;\nsetp.ne.u32 p, %0, 0;\n@p bar.arrive " #id ", 256;\n}" ::"r"((uint32_t)(who)) : "memory")

__device__ __forceinline__ void ld128(const void* p, uint32_t& x, uint32_t& y, uint32_t& z, uint32_t& w) {
  asm volatile("ld.relaxed.gpu.global.v4.b32 {%0, %1, %2, %3}, [%4];" : "=r"(x), "=r"(y), "=r"(z), "=r"(w) : "l"(p) : "memory");
}
__device__ __forceinline__ void ld128_if(const void* p, uint4& v, uint32_t P) {
  asm volatile("{\n.reg .b32 t;\n.reg .b64 a, b;\n.reg .pred p;\nlop3.b32 t, %1, %5, 1, 0x28;\nsetp.ne.u32 p, t, 0;\n@p ld.relaxed.gpu.global.v4.b32 {%0, %1, %2, %3}, [%4];\n}"
               : "+r"(v.x), "+r"(v.y), "+r"(v.z), "+r"(v.w) : "l"(p), "r"(P) : "memory");
}
__device__ __forceinline__ void st128(void* p, uint32_t x, uint32_t y, uint32_t z, uint32_t w) {
  asm volatile("st.relaxed.gpu.global.v4.b32 [%0], {%1, %2, %3, %4};" ::"l"(p), "r"(x), "r"(y), "r"(z), "r"(w) : "memory");
}
__device__ __forceinline__ void ld64(const uint2* p, uint32_t& x, uint32_t& y) {
  asm volatile("ld.relaxed.gpu.global.v2.b32 {%0, %1}, [%2];" : "=r"(x), "=r"(y) : "l"(p) : "memory");
}
__device__ __forceinline__ void st64(void* p, uint32_t x, uint32_t y) {
  asm volatile("st.relaxed.gpu.global.v2.b32 [%0], {%1, %2};" ::"l"(p), "r"(x), "r"(y) : "memory");
}
__device__ __forceinline__ uint32_t pack(float lo, float hi) {
  uint32_t r;
  asm("cvt.rn.bf16x2.f32 %0, %1, %2;" : "=r"(r) : "f"(hi), "f"(lo));
  return r;
}
__device__ __forceinline__ float blo(uint32_t w) { return __uint_as_float(w << 16); }
__device__ __forceinline__ float bhi(uint32_t w) { return __uint_as_float(w & 0xFFFF0000u); }
__device__ __forceinline__ float ex2(float x) { float r; asm("ex2.approx.ftz.f32 %0, %1;" : "=f"(r) : "f"(x)); return r; }
__device__ __forceinline__ float rcp(float x) { float r; asm("rcp.approx.ftz.f32 %0, %1;" : "=f"(r) : "f"(x)); return r; }
__device__ __forceinline__ float tanh_(float x) { float r; asm("tanh.approx.f32 %0, %1;" : "=f"(r) : "f"(x)); return r; }
__device__ __forceinline__ float rsq(float x) { float r; asm("rsqrt.approx.ftz.f32 %0, %1;" : "=f"(r) : "f"(x)); return r; }
__device__ __forceinline__ void ldsm4(uint32_t a, uint32_t& r0, uint32_t& r1, uint32_t& r2, uint32_t& r3) {
  asm volatile("ldmatrix.sync.aligned.m8n8.x4.shared.b16 {%0,%1,%2,%3}, [%4];" : "=r"(r0), "=r"(r1), "=r"(r2), "=r"(r3) : "r"(a) : "memory");
}
__device__ __forceinline__ uint32_t lds32(uint32_t a) {
  uint32_t v;
  asm volatile("ld.shared.u32 %0, [%1];" : "=r"(v) : "r"(a) : "memory");
  return v;
}
__device__ __forceinline__ void ldsm2(uint32_t a, uint32_t& r0, uint32_t& r1) {
  asm volatile("ldmatrix.sync.aligned.m8n8.x2.shared.b16 {%0,%1}, [%2];" : "=r"(r0), "=r"(r1) : "r"(a) : "memory");
}
__device__ __forceinline__ void stsm4(uint32_t a, uint32_t r0, uint32_t r1, uint32_t r2, uint32_t r3) {
  asm volatile("stmatrix.sync.aligned.m8n8.x4.shared.b16 [%0], {%1,%2,%3,%4};" ::"r"(a), "r"(r0), "r"(r1), "r"(r2), "r"(r3) : "memory");
}
__device__ __forceinline__ bool mbar_test(uint32_t a, uint32_t ph) {
  uint32_t r;
  asm volatile("{\n.reg .pred p;\nmbarrier.test_wait.parity.shared::cta.b64 p, [%1], %2;\nselp.u32 %0, 1, 0, p;\n}" : "=r"(r) : "r"(a), "r"(ph) : "memory");
  return r;
}
__device__ __forceinline__ void sts128(uint32_t a, uint32_t x, uint32_t y, uint32_t z, uint32_t w) {
  asm volatile("st.shared.v4.u32 [%0], {%1,%2,%3,%4};" ::"r"(a), "r"(x), "r"(y), "r"(z), "r"(w) : "memory");
}
__device__ __forceinline__ void sts64(uint32_t a, uint32_t x, uint32_t y) {
  asm volatile("st.shared.v2.u32 [%0], {%1,%2};" ::"r"(a), "r"(x), "r"(y) : "memory");
}
__device__ __forceinline__ void lds64(uint32_t a, uint32_t& x, uint32_t& y) {
  asm volatile("ld.shared.v2.u32 {%0,%1}, [%2];" : "=r"(x), "=r"(y) : "r"(a) : "memory");
}

__device__ __forceinline__ void lds128(uint32_t a, uint32_t& x, uint32_t& y, uint32_t& z, uint32_t& w) {
  asm volatile("ld.shared.v4.u32 {%0,%1,%2,%3}, [%4];" : "=r"(x), "=r"(y), "=r"(z), "=r"(w) : "r"(a) : "memory");
}
struct Ring {
  uint32_t sb;
  uint32_t ebar;
  __device__ __forceinline__ void acquire(int slot, uint32_t ph) { mbar_wait_c(sb + BAR_FULL + slot * 8, ph); }
  __device__ __forceinline__ void acquire_s(int slot, uint32_t ph) { mbar_wait(sb + BAR_FULL + slot * 8, ph); }
  __device__ __forceinline__ void acquire2(int slot, uint32_t ph) { mbar_wait2(sb + BAR_FULL + slot * 8, ph); }
  __device__ __forceinline__ void release(int slot) { if (ebar) mbar_arrive_cl(ebar + slot * 8); }
};
#define sdesc(slot) mkdesc((slot) * kStageBytes)
#define ddesc(slot) Desc{dz + (slot < 4 ? slot * (kStageBytes >> 4) : (OFF_E >> 4) + (slot - 4) * (kLBytes >> 4)), 64}
constexpr uint32_t kBoxD = kBoxBytes >> 4;

__device__ __forceinline__ constexpr int koff(int k) { return k < 3 ? k * 128 : k < 6 ? 448 + (k - 3) * 128 : 384; }
template <int B, int K0 = 0, int K1 = 7, bool ACC = false>
__device__ __forceinline__ void box_mma(float (&d)[28], const uint32_t (&A)[112], Desc db) {
#pragma unroll
  for (int k = K0; k < (K1 < 6 ? K1 : 6); k++) wgmma_rs_n56(d, A[28 * B + 4 * k], A[28 * B + 4 * k + 1], A[28 * B + 4 * k + 2], A[28 * B + 4 * k + 3], db + koff(k), ACC || !(B == 0 && k == 0));
  if (K1 == 7) wgmma_rs_n56_w(d, A[28 * B + 24], A[28 * B + 25], A[28 * B + 26], A[28 * B + 27], db + koff(6));
}
template <int HALF, bool ACC = false>
__device__ __forceinline__ void stage_a(float (&d)[28], const uint32_t (&A)[112], Ring& rg, int slot, Desc db, uint32_t ph, int prev) {
  rg.acquire_s(slot, ph);
  WG_FENCE;
  box_mma<2 * HALF, 0, 7, ACC>(d, A, db);
  WG_COMMIT;
  WG_WAIT(1);
  if (prev >= 0) rg.release(prev);
}
template <int HALF, bool SF = true>
__device__ __forceinline__ void stage_b(float (&d)[28], const uint32_t (&A)[112], Desc db) {
  WG_FENCE;
  box_mma<2 * HALF + 1>(d, A, db + kBoxD);
  WG_COMMIT;
  if (SF) SCHED_FENCE();
}
template <int HALF, bool ACC = false>
__device__ __forceinline__ void stage(float (&d)[28], const uint32_t (&A)[112], Ring& rg, int slot, Desc db, uint32_t ph, int prev) {
  stage_a<HALF, ACC>(d, A, rg, slot, db, ph, prev);
  stage_b<HALF>(d, A, db);
}
__device__ __forceinline__ void drain(Ring& rg, int slot) { WG_WAIT(0); rg.release(slot); }

__device__ __forceinline__ void phi_proj(float (&p)[28], const float (&d)[28], uint64_t dz) {
  uint32_t a[14];
#pragma unroll
  for (int i = 0; i < 14; i++) a[i] = pack(d[2 * i], d[2 * i + 1]);
  WG_FENCE;
#pragma unroll
  for (int k = 0; k < 3; k++) wgmma_rs_n56(p, a[4 * k], a[4 * k + 1], a[4 * k + 2], a[4 * k + 3], mkdesc(OFF_WP) + k * 128, k != 0);
  wgmma_rs_n56(p, a[12], a[13], 0u, 0u, mkdesc(OFF_WP) + 384, true);
  WG_COMMIT;
}
template <int K0 = 0, int K1 = 28>
__device__ __forceinline__ void colsum(float (&d)[4], Desc da, uint32_t ones = OFF_ONES) {
  WG_FENCE;
#pragma unroll
  for (int k = K0; k < K1; k++) wgmma_mo_n8(d, da + k * 128, (1024 + ones) >> 4, k != 0);
  WG_COMMIT;
}
__device__ __forceinline__ void put_cs(const float (&q)[4], uint32_t a, uint32_t bar, int warp, int lane) {
  a += (warp & 3) * 64 + (lane >> 2) * 4;
  if (!(lane & 3)) {
    asm volatile("st.shared.f32 [%0], %1;" ::"r"(a), "f"(q[0]) : "memory");
    asm volatile("st.shared.f32 [%0], %1;" ::"r"(a + 32), "f"(q[2]) : "memory");
  }
  __syncwarp();
  if (lane == 0) mbar_arrive(bar);
}
template <uint32_t D>
__device__ __forceinline__ void delay() {
  if (D) {
    uint32_t t0, t1;
    asm volatile("mov.u32 %0, %%clock;" : "=r"(t0));
    do { asm volatile("mov.u32 %0, %%clock;" : "=r"(t1)); } while (t1 - t0 < D);
  }
}
__device__ __forceinline__ void quad_tr(uint32_t (&v)[4], int t) {
  const bool t1 = t & 1, t2 = t & 2;
  uint32_t a = __shfl_xor_sync(~0u, t1 ? v[0] : v[1], 1), b = __shfl_xor_sync(~0u, t1 ? v[2] : v[3], 1);
  if (t1) { v[0] = a; v[2] = b; } else { v[1] = a; v[3] = b; }
  a = __shfl_xor_sync(~0u, t2 ? v[0] : v[2], 2); b = __shfl_xor_sync(~0u, t2 ? v[1] : v[3], 2);
  if (t2) { v[0] = a; v[1] = b; } else { v[2] = a; v[3] = b; }
}
__device__ __forceinline__ float quad_stat(float s0, float s1, float q0, float q1, int t) {
  const bool hi = t & 2, od = t & 1;
  const float ks = (hi ? s1 : s0) + __shfl_xor_sync(~0u, hi ? s0 : s1, 2);
  const float kq = (hi ? q1 : q0) + __shfl_xor_sync(~0u, hi ? q0 : q1, 2);
  return (od ? kq : ks) + __shfl_xor_sync(~0u, od ? ks : kq, 1);
}
__device__ __forceinline__ uint32_t lop_7e(uint32_t a, uint32_t b, uint32_t c) {
  uint32_t r;
  asm("lop3.b32 %0, %1, %2, %3, 0x7E;" : "=r"(r) : "r"(a), "r"(b), "r"(c));
  return r;
}
__device__ __forceinline__ void mark14(uint32_t (&R)[14], uint32_t P) {
#pragma unroll
  for (int i = 0; i < 14; i += 4) R[i] = (R[i] & ~1u) | P;
}
struct Xa {
  uint32_t l16;
  uint32_t o16;
  uint32_t l8, o8;
  uint32_t xf;
  int lane;
  uint32_t tsa;
};
__device__ __forceinline__ void hint(uint32_t* flag, uint32_t tag, const Xa& xa) {
  __syncwarp();
  if (xa.lane == 0) st32(flag, tag);
}
__device__ __forceinline__ void stg14(Half* u, const uint32_t (&R)[14], const Xa& xa) {
  uint8_t* p = u->b + xa.o16;
  st128(p, R[0], R[1], R[2], R[3]);
  st128(p + 512, R[4], R[5], R[6], R[7]);
  st128(p + 1024, R[8], R[9], R[10], R[11]);
  st64(u->b + xa.o8, R[12], R[13]);
}
__device__ __forceinline__ void ldg14(uint32_t (&R)[14], const Half* u, const Xa& xa) {
#pragma unroll
  for (int i = 0; i < 3; i++) ld128(u->b + xa.o16 + i * 512, R[4 * i], R[4 * i + 1], R[4 * i + 2], R[4 * i + 3]);
  ld64((const uint2*)(u->b + xa.o8), R[12], R[13]);
}
__device__ __forceinline__ void send14(Half* u, uint32_t* flag, uint32_t tag, const uint32_t (&R)[14], const Xa& xa) {
  stg14(u, R, xa);
  hint(flag, tag, xa);
}
__device__ __forceinline__ void lds14(uint32_t* q, uint32_t& h0, uint32_t& h1, int slot, const Xa& xa) {
#pragma unroll
  for (int i = 0; i < 3; i++) lds128(xa.l16 + slot * kSlot + i * 512, q[4 * i], q[4 * i + 1], q[4 * i + 2], q[4 * i + 3]);
  lds64(xa.l8 + slot * kSlot, h0, h1);
}
__device__ __forceinline__ void sts14(const uint32_t (&h)[14], int slot, const Xa& xa) {
#pragma unroll
  for (int i = 0; i < 3; i++) sts128(xa.l16 + slot * kSlot + i * 512, h[4 * i], h[4 * i + 1], h[4 * i + 2], h[4 * i + 3]);
  sts64(xa.l8 + slot * kSlot, h[12], h[13]);
}
template <int B, int W = 1>
__device__ __forceinline__ void ld_box(uint32_t (&A)[112], uint32_t ph, const Xa& xa, int tsi = 0) {
  if (W == 2) mbar_wait2(xa.xf + 8 * B, ph); else if (W) mbar_wait_c(xa.xf + 8 * B, ph);
  if (B > 0) lds14(&A[28 * B], A[28 * B + 24], A[28 * B + 25], 2 * B - 1, xa);
  lds14(&A[28 * B + 12], A[28 * B + 26], A[28 * B + 27], 2 * B, xa);
}
template <int B>
__device__ __forceinline__ void ck_box(uint32_t (&A)[112], uint32_t P, const Half* u0, int key, const Xa& xa) {
  const uint8_t* gb = u0->b + xa.o16;
  if (B > 0) {
    asm volatile("{\n.reg .pred p;\n.reg .b32 m, n, t, u, v, w;\n.reg .b64 ga, gb;\nmov.b32 n, 0;\nmov.b32 m, 0;\nLC:\nlop3.b32 t, %0, %4, %28, 0x7E;\nlop3.b32 u, %8, %12, %28, 0x7E;\nlop3.b32 v, %14, %18, %28, 0x7E;\nlop3.b32 w, %22, %26, %28, 0x7E;\nlop3.b32 t, t, u, v, 0xFE;\nlop3.b32 t, t, w, 1, 0xA8;\nsetp.gt.u32 p, t, n;\nvote.sync.any.pred p, p, -1;\n@!p bra LD;\nxor.b32 v, %30, %32+0;\nmad.wide.u32 ga, v, 7680, %29;\nmad.wide.u32 gb, %31, 1, ga;\nld.relaxed.gpu.global.v2.b32 {%12,%13}, [gb];\nld.relaxed.gpu.global.v4.b32 {%0,%1,%2,%3}, [ga+0];\nld.relaxed.gpu.global.v4.b32 {%4,%5,%6,%7}, [ga+512];\nld.relaxed.gpu.global.v4.b32 {%8,%9,%10,%11}, [ga+1024];\nxor.b32 v, %30, %32+1;\nmad.wide.u32 ga, v, 7680, %29;\nmad.wide.u32 gb, %31, 1, ga;\nld.relaxed.gpu.global.v2.b32 {%26,%27}, [gb];\nld.relaxed.gpu.global.v4.b32 {%14,%15,%16,%17}, [ga+0];\nld.relaxed.gpu.global.v4.b32 {%18,%19,%20,%21}, [ga+512];\nld.relaxed.gpu.global.v4.b32 {%22,%23,%24,%25}, [ga+1024];\nadd.u32 m, m, 1;\nshr.u32 n, m, 16;\nbra LC;\nLD:\n}"
        : "+r"(A[28 * B + 0]), "+r"(A[28 * B + 1]), "+r"(A[28 * B + 2]), "+r"(A[28 * B + 3]), "+r"(A[28 * B + 4]), "+r"(A[28 * B + 5]), "+r"(A[28 * B + 6]), "+r"(A[28 * B + 7]), "+r"(A[28 * B + 8]), "+r"(A[28 * B + 9]), "+r"(A[28 * B + 10]), "+r"(A[28 * B + 11]), "+r"(A[28 * B + 24]), "+r"(A[28 * B + 25]), "+r"(A[28 * B + 12]), "+r"(A[28 * B + 13]), "+r"(A[28 * B + 14]), "+r"(A[28 * B + 15]), "+r"(A[28 * B + 16]), "+r"(A[28 * B + 17]), "+r"(A[28 * B + 18]), "+r"(A[28 * B + 19]), "+r"(A[28 * B + 20]), "+r"(A[28 * B + 21]), "+r"(A[28 * B + 22]), "+r"(A[28 * B + 23]), "+r"(A[28 * B + 26]), "+r"(A[28 * B + 27])
        : "r"(P), "l"(gb), "r"(key), "r"(xa.o8 - xa.o16), "n"(2 * B) : "memory");
  } else {
    asm volatile("{\n.reg .pred p;\n.reg .b32 m, n, t, u, v, w;\n.reg .b64 ga, gb;\nmov.b32 n, 0;\nmov.b32 m, 0;\nLC:\nlop3.b32 t, %0, %4, %14, 0x7E;\nlop3.b32 u, %8, %12, %14, 0x7E;\nlop3.b32 t, t, u, 1, 0xA8;\nsetp.gt.u32 p, t, n;\nvote.sync.any.pred p, p, -1;\n@!p bra LD;\nxor.b32 v, %16, %18+0;\nmad.wide.u32 ga, v, 7680, %15;\nmad.wide.u32 gb, %17, 1, ga;\nld.relaxed.gpu.global.v2.b32 {%12,%13}, [gb];\nld.relaxed.gpu.global.v4.b32 {%0,%1,%2,%3}, [ga+0];\nld.relaxed.gpu.global.v4.b32 {%4,%5,%6,%7}, [ga+512];\nld.relaxed.gpu.global.v4.b32 {%8,%9,%10,%11}, [ga+1024];\nadd.u32 m, m, 1;\nshr.u32 n, m, 16;\nbra LC;\nLD:\n}"
        : "+r"(A[12]), "+r"(A[13]), "+r"(A[14]), "+r"(A[15]), "+r"(A[16]), "+r"(A[17]), "+r"(A[18]), "+r"(A[19]), "+r"(A[20]), "+r"(A[21]), "+r"(A[22]), "+r"(A[23]), "+r"(A[26]), "+r"(A[27])
        : "r"(P), "l"(gb), "r"(key), "r"(xa.o8 - xa.o16), "n"(1) : "memory");
  }
}
template <int B>
__device__ __forceinline__ void ck_two(uint32_t (&A)[112], uint32_t P, const Half* u0, int key0, int key1, const Xa& xa, int id = 0) {
  constexpr int o = 28 * B;
  uint32_t t = lop_7e(A[o + 12], A[o + 16], P) | lop_7e(A[o + 20], A[o + 26], P) | lop_7e(A[o + 28], A[o + 32], P);
  if (B) t |= lop_7e(A[o], A[o + 4], P) | lop_7e(A[o + 8], A[o + 24], P);
  t |= lop_7e(A[o + 36], A[o + 52], P) | lop_7e(A[o + 40], A[o + 44], P) | lop_7e(A[o + 48], A[o + 54], P);
  asm volatile("" : "+r"(t));
  if (__builtin_expect(__any_sync(~0u, t & 1), 0)) { ck_box<B>(A, P, u0, key0, xa); ck_box<B + 1>(A, P, u0, key1, xa); }
}
template <int BAR, uint32_t D, bool ST = true>
__device__ __forceinline__ void pull(const Half* gx, const uint32_t* fl, uint32_t tag, int c, int b, int wg, uint32_t lz, const Xa& xa) {
  b ^= c >> 1;
  const int src = b ? (c & ~1) ^ (2 * b) : c ^ 1;
  fl += 4 * src + (xa.lane & (b ? 7 : 3));
  constexpr uint32_t U = ST ? kSlot : kUnit;
  const uint32_t bar = xa.xf + 8 * b, dst = lz + (b ? 2 * b - 1 : 0) * kSlot;
  const uint8_t* g = gx[src].b;
  if (elect()) { mbar_expect(bar, b ? 2 * U : U); mbar_arrive(bar); }
  asm volatile("" ::"r"(bar), "r"(dst), "l"(g));
  delay<D>();
#pragma unroll 1
  for (int n = 0; n < kSpin; n++) {
    if (!__any_sync(~0u, ld32(fl) != tag)) break;
  }
  if (BAR && wg == 1) asm volatile("bar.sync %0, 256;" ::"n"(BAR) : "memory");
#define BULK(o, n) asm volatile("{\n.reg .pred p;\nelect.sync _|p, -1;\n@p cp.async.bulk.shared::cluster.global.mbarrier::complete_tx::bytes [%0], [%1], %2, [%3];\n}" ::"r"(dst + (o)), "l"(g + (o)), "r"(n), "r"(bar) : "memory")
  BULK(0, U);
  if (b) BULK(kSlot, U);
  if (BAR && wg == 0) asm volatile("bar.arrive %0, 256;" ::"n"(BAR) : "memory");
}
__device__ __forceinline__ void own_to_A(uint32_t (&A)[112], const uint32_t (&R)[14]) {
#pragma unroll
  for (int i = 0; i < 12; i++) A[i] = R[i];
  A[24] = R[12]; A[25] = R[13];
}
__device__ __forceinline__ uint32_t packh(float lo, float hi) {
  uint32_t r;
  asm("cvt.rn.f16x2.f32 %0, %1, %2;" : "=r"(r) : "f"(hi), "f"(lo));
  return r;
}
template <int I0 = 0, int I1 = 14>
__device__ __forceinline__ void glu_gate(uint32_t (&T)[14], const float (&d0)[28]) {
#pragma unroll
  for (int i = I0; i < I1; i++) T[i] = packh(tanh_(d0[2 * i]), tanh_(d0[2 * i + 1]));
}
__device__ __forceinline__ void glu_up(uint32_t (&h)[14], const uint32_t (&T)[14], const float (&d1)[28]) {
#pragma unroll
  for (int i = 0; i < 14; i++) {
    const float2 t = __half22float2(*(const __half2*)&T[i]);
    h[i] = pack(fmaf(d1[2 * i], t.x, d1[2 * i]), fmaf(d1[2 * i + 1], t.y, d1[2 * i + 1]));
  }
}
__device__ __forceinline__ uint32_t bfma(uint32_t a, uint32_t b, uint32_t c) {
  uint32_t r;
  asm("fma.rn.bf16x2 %0, %1, %2, %3;" : "=r"(r) : "r"(a), "r"(b), "r"(c));
  return r;
}
template <int B>
__device__ __forceinline__ void nm_box(uint32_t (&A)[112], uint32_t s0, uint32_t s1, uint32_t b0, uint32_t b1) {
#pragma unroll
  for (int i = 14 * B; i < 14 * B + 14; i++) { A[2 * i] = bfma(A[2 * i], s0, b0); A[2 * i + 1] = bfma(A[2 * i + 1], s1, b1); }
}
__device__ __forceinline__ void send_kv(uint4* p1, float (&e)[32], bool isB, int t, uint32_t P) {
  if (isB == (t < 2)) { e[13] = e[28]; e[15] = e[30]; }
#pragma unroll
  for (int hh = 0; hh < 2; hh++) {
    uint32_t w[4];
#pragma unroll
    for (int jj = 0; jj < 4; jj++) {
      const uint32_t a = pack(e[4 * jj + 2 * hh], e[4 * jj + 2 * hh + 1]), b = pack(e[4 * jj + 12 + 2 * hh], e[4 * jj + 13 + 2 * hh]);
      w[jj] = isB ? b : a;
    }
    st128(p1 + hh * 8, w[0], (w[1] & ~1u) | P, w[2], w[3]);
  }
}
template <bool HINT = true>
__device__ __forceinline__ void send_acc(Half* idx, uint32_t* flag, uint32_t tag, const float (&d)[28], uint32_t P, const Xa& xa) {
  uint32_t pr[14];
#pragma unroll
  for (int e = 0; e < 14; e++) pr[e] = pack(d[2 * e], d[2 * e + 1]);
  mark14(pr, P);
  stg14(idx, pr, xa);
  if (HINT) hint(flag, tag, xa);
}

template <int B>
__device__ __forceinline__ void ldx_box(uint32_t (&A)[112], uint32_t xl, uint32_t x6, uint32_t xf, uint32_t mhi, uint32_t l7) {
  mbar_wait_c(xf + 8 * B, 0);
#pragma unroll
  for (int k = 0; k < 7; k++) {
    const int s = B * 7 + k;
    const int b0 = k < 3 ? 14 * B + 2 * k : k < 6 ? 14 * B + 7 + 2 * (k - 3) : 14 * B + 6, b1 = k < 6 ? b0 + 1 : b0 + 7;
    const uint32_t a0 = (b0 < 48 ? xl + (b0 >> 3) * 8192 : x6) + (((b0 & 7) ^ l7) << 4), a1 = (b1 < 48 ? xl + (b1 >> 3) * 8192 : x6) + (((b1 & 7) ^ l7) << 4);
    ldsm4(mhi ? a1 : a0, A[4 * s], A[4 * s + 1], A[4 * s + 2], A[4 * s + 3]);
  }
}
template <bool ALL = false>
__device__ __forceinline__ void row_stats(uint32_t (&sv)[8], float stat, uint32_t P, const Half* gx, int c, int tid, float& m0, float& e0, float& m1, float& e1) {
  if (!ALL) sv[7] = __float_as_uint(stat);
#pragma unroll 1
  for (int n = 0; n < kSpin; n++) {
    if (!__any_sync(~0u, (lop_7e(sv[0], sv[1], P) | lop_7e(sv[2], sv[3], P) | lop_7e(sv[4], sv[5], P) | lop_7e(sv[6], sv[7], P)) & 1)) break;
#pragma unroll
    for (int i = 0; i < (ALL ? 8 : 7); i++) sv[i] = ld32((const uint32_t*)(gx[ALL ? i : (i ? c & ~1 : c) ^ (i + 1)].b + kUnit) + (tid & 127));
  }
  float v[8];
#pragma unroll
  for (int i = 0; i < 8; i++) v[i] = __uint_as_float(sv[i]);
  const float S = (((v[0] + v[1]) + (v[2] + v[3])) + ((v[4] + v[5]) + (v[6] + v[7]))) * (1.f / 448.f);
  const int qb = tid & 28;
  m0 = __shfl_sync(~0u, S, qb); e0 = __shfl_sync(~0u, S, qb + 1); m1 = __shfl_sync(~0u, S, qb + 2); e1 = __shfl_sync(~0u, S, qb + 3);
}
template <bool ST>
__device__ __forceinline__ void front(float (&d)[28], uint32_t (&A)[112], Desc s0, Desc s1, Ring& rg, int rel, uint32_t ph, uint32_t P, uint32_t Ps, const Half* gx,
                                      int c, int tid, uint32_t lz, const Xa& xa, int ts, float stat, float& m0, float& e0, float& m1, float& e1) {
  const int c1 = c & ~1;
  uint32_t sv[8];
  ld_box<0>(A, ph, xa, ts); ld_box<1>(A, ph, xa, ts ? ts + 1 : 0);
  if (rel == 0) rg.release(3);
  ld_box<2, 2>(A, ph, xa, ts ? ts + 2 : 0); ld_box<3, 0>(A, ph, xa);
  if (rel < 0) { rg.release(2); rg.release(3); }
  ck_two<0>(A, P, gx, c, c1, xa, rel + 1);
  WG_FENCE; box_mma<0, 3>(d, A, s0); box_mma<1>(d, A, s0 + kBoxD); WG_COMMIT;
  if (ST) {
#pragma unroll
    for (int i = 0; i < 7; i++) sv[i] = lds32(lz + kUnit + (tid & 127) * 4 + i * kSlot);
  }
  ck_two<2>(A, P, gx, c1, c1, xa, rel + 1);
  WG_FENCE; box_mma<2>(d, A, s1); WG_COMMIT;
  if (rel >= 0) { WG_WAIT(1); rg.release(rel); }
  if (ST) { row_stats(sv, stat, Ps, gx, c, tid, m0, e0, m1, e1); WG_FENCE; }
  box_mma<3>(d, A, s1 + kBoxD); WG_COMMIT;
}
__device__ __forceinline__ void fold_ln(float (&d)[28], uint32_t csa, float f0, float f1, float o0, float o1) {
#pragma unroll
  for (int i = 0; i < 7; i++) {
    uint32_t x, y;
    lds64(csa + i * 32, x, y);
    d[4 * i] = fmaf(d[4 * i], f0, o0 * __uint_as_float(x)); d[4 * i + 1] = fmaf(d[4 * i + 1], f0, o0 * __uint_as_float(y));
    d[4 * i + 2] = fmaf(d[4 * i + 2], f1, o1 * __uint_as_float(x)); d[4 * i + 3] = fmaf(d[4 * i + 3], f1, o1 * __uint_as_float(y));
  }
}
#define PIN28(a) _Pragma("unroll") for (int i = 0; i < 28; i++) asm volatile("" : "+f"(a[i]))
__device__ __forceinline__ void sm_a(float (&p)[28], float (&e)[28], float L0, float L1) {
  float mx0 = fmaxf(p[0], p[1]), mn0 = fminf(p[0], p[1]), mx1 = fmaxf(p[2], p[3]), mn1 = fminf(p[2], p[3]);
#pragma unroll
  for (int j = 1; j < 7; j++) {
    mx0 = fmaxf(mx0, fmaxf(p[4 * j], p[4 * j + 1])); mn0 = fminf(mn0, fminf(p[4 * j], p[4 * j + 1]));
    mx1 = fmaxf(mx1, fmaxf(p[4 * j + 2], p[4 * j + 3])); mn1 = fminf(mn1, fminf(p[4 * j + 2], p[4 * j + 3]));
  }
  mx0 = fmaxf(mx0, __shfl_xor_sync(~0u, mx0, 1)) * -L0; mx1 = fmaxf(mx1, __shfl_xor_sync(~0u, mx1, 1)) * -L1;
  mn0 = fminf(mn0, __shfl_xor_sync(~0u, mn0, 1)) * L0; mn1 = fminf(mn1, __shfl_xor_sync(~0u, mn1, 1)) * L1;
#pragma unroll
  for (int i = 0; i < 28; i++) {
    e[i] = (i & 2) ? ex2(fmaf(p[i], L1, mx1)) : ex2(fmaf(p[i], L0, mx0));
    p[i] = (i & 2) ? fmaf(p[i], -L1, mn1) : fmaf(p[i], -L0, mn0);
  }
  PIN28(e); PIN28(p);
}
__device__ __forceinline__ void sm_norm(uint32_t* o, float (&a)[28]) {
  PIN28(a);
  float s[4] = {a[0], a[1], a[2], a[3]};
#pragma unroll
  for (int i = 4; i < 28; i++) s[i & 3] += a[i];
  float s0 = s[0] + s[1], s1 = s[2] + s[3];
  s0 = rcp(s0 + __shfl_xor_sync(~0u, s0, 1)); s1 = rcp(s1 + __shfl_xor_sync(~0u, s1, 1));
#pragma unroll
  for (int i = 0; i < 14; i++) o[i] = (i & 1) ? pack(a[2 * i] * s1, a[2 * i + 1] * s1) : pack(a[2 * i] * s0, a[2 * i + 1] * s0);
}
__device__ __forceinline__ void sm_b(float (&p)[28], float (&e)[28], uint32_t (&o)[16], uint32_t pa, uint32_t mhi, uint32_t l7) {
  PIN28(p);
#pragma unroll
  for (int i = 0; i < 28; i++) p[i] = ex2(p[i]);
  sm_norm(o, e);
#pragma unroll
  for (int b = 0; b < 6; b += 2) stsm4(pa + (((b + mhi) ^ l7) << 4), o[2 * b], o[2 * b + 1], o[2 * b + 2], o[2 * b + 3]);
  o[0] = o[12]; o[1] = o[13];
  PIN28(p);
}
__device__ __forceinline__ void sm_c(float (&p)[28], uint32_t (&o)[16], uint32_t pa, uint32_t mhi, uint32_t l7) {
  sm_norm(o + 2, p);
  stsm4(pa + (((6 + mhi) ^ l7) << 4), o[0], o[1], o[2], o[3]);
#pragma unroll
  for (int b = 0; b < 6; b += 2) stsm4(pa + 8192 + (((b + mhi) ^ l7) << 4), o[2 * b + 4], o[2 * b + 5], o[2 * b + 6], o[2 * b + 7]);
}
__device__ __forceinline__ void publish(uint32_t (&A)[112], uint32_t (&xr)[14], float& stat, const float (&d)[28], Half* u, uint32_t* fl, int c, uint32_t tag, uint32_t Px, uint32_t Ps, int tid, const Xa& xa) {
  uint32_t R[14];
#pragma unroll
  for (int i = 0; i < 14; i++) R[i] = xr[i] = pack(d[2 * i], d[2 * i + 1]);
  mark14(R, Px);
  stg14(u, R, xa);
  own_to_A(A, R);
  hint(fl + 4 * c + ((tid >> 5) & 3), tag, xa);
  SCHED_FENCE();
  float s0 = 0.f, s1 = 0.f, q0 = 0.f, q1 = 0.f;
#pragma unroll
  for (int j = 0; j < 7; j++) {
    s0 += d[4 * j] + d[4 * j + 1]; s1 += d[4 * j + 2] + d[4 * j + 3];
    q0 = fmaf(d[4 * j], d[4 * j], fmaf(d[4 * j + 1], d[4 * j + 1], q0));
    q1 = fmaf(d[4 * j + 2], d[4 * j + 2], fmaf(d[4 * j + 3], d[4 * j + 3], q1));
  }
  const uint32_t v = (__float_as_uint(quad_stat(s0, s1, q0, q1, tid & 3)) & ~1u) | Ps;
  st32((uint32_t*)(u->b + kUnit) + (tid & 127), v);
  stat = __uint_as_float(v);
}

#define TSS 2
__device__ __forceinline__ void kv_hop1(Scratch* gs, int c, int r, int w, int lane, uint32_t L) {
  const uint32_t P = L ^ 1;
  const uint4* p1 = &gs->kv1[c][r][lane >> 3][8 * w + (lane & 7)];
  uint4 u[4] = {};
#pragma unroll
  for (int i = 0; i < 4; i++) u[i].y = L;
  const bool h1 = lane & 16, h0 = lane & 8;
  uint32_t* o = (uint32_t*)&gs->kv2[c][(w >> 1) * 64 + (r >> 2) * 16 + (w & 1) * 8 + (r & 3) * 2 + ((lane >> 2) & 1)][lane >> 3] + (lane & 3);
  delay<DK1>();
#pragma unroll 1
  for (int n = 0; n < kSpin; n++) {
#pragma unroll
    for (int i = 0; i < 4; i++) ld128_if(p1 + i * 128, u[i], P);
    if (!__any_sync(~0u, (lop_7e(u[0].y, u[1].y, P) | lop_7e(u[2].y, u[3].y, P)) & 1)) break;
  }
  float a[8];
  a[0] = (blo(u[0].x) + blo(u[1].x)) + (blo(u[2].x) + blo(u[3].x)); a[1] = (bhi(u[0].x) + bhi(u[1].x)) + (bhi(u[2].x) + bhi(u[3].x));
  a[2] = (blo(u[0].y) + blo(u[1].y)) + (blo(u[2].y) + blo(u[3].y)); a[3] = (bhi(u[0].y) + bhi(u[1].y)) + (bhi(u[2].y) + bhi(u[3].y));
  a[4] = (blo(u[0].z) + blo(u[1].z)) + (blo(u[2].z) + blo(u[3].z)); a[5] = (bhi(u[0].z) + bhi(u[1].z)) + (bhi(u[2].z) + bhi(u[3].z));
  a[6] = (blo(u[0].w) + blo(u[1].w)) + (blo(u[2].w) + blo(u[3].w)); a[7] = (bhi(u[0].w) + bhi(u[1].w)) + (bhi(u[2].w) + bhi(u[3].w));
#pragma unroll
  for (int i = 0; i < 4; i++) a[i] = (h1 ? a[i + 4] : a[i]) + __shfl_xor_sync(~0u, h1 ? a[i] : a[i + 4], 16);
#pragma unroll
  for (int i = 0; i < 2; i++) a[i] = (h0 ? a[i + 2] : a[i]) + __shfl_xor_sync(~0u, h0 ? a[i] : a[i + 2], 8);
  const uint32_t v = pack(a[0], a[1]);
  st32(o, (lane & 3) == 1 ? (v & ~1u) | P : v);
}
struct Maps { CUtensorMap m[6]; };
#define tm_x tm.m[0]
#define tm_qkv tm.m[1]
template <bool SM>
__global__ void __cluster_dims__(2, 1, 1) __launch_bounds__(384, 1)
fused_kernel(Scratch* gs, const __nv_bfloat16* __restrict__ w_phi, const __nv_bfloat16* __restrict__ w_qkv, const __nv_bfloat16* __restrict__ w_d,
             uint4* wd, int zero, const __grid_constant__ Maps tm, const __nv_bfloat16* __restrict__ w_g, const __nv_bfloat16* __restrict__ w_u,
             const __nv_bfloat16* __restrict__ w_o, __nv_bfloat16* __restrict__ out, const __grid_constant__ Dz dzs) {
  uint64_t dz = dzs.z[0];
  asm volatile(".reg .b32 spin;\nmov.b32 spin, %0;" ::"n"(kSpin));
  extern __shared__ __align__(1024) uint8_t smem[];
  const uint32_t sb = 1024 + ((blockIdx.x & 1) << 24);
  const int tid = threadIdx.x, lane = tid & 31, warp = __shfl_sync(~0u, tid >> 5, 0);
  const int rank = blockIdx.x & 1;
  int tpc, wish;
  asm("mov.u32 %0, %%smid;" : "=r"(tpc));
  tpc = SM ? (tpc >> 1) + WISH : ((blockIdx.x >> 1) + 60) & 63;
  const int j7 = ((tpc - 32) * 37) >> 8;
  asm("{\n.reg .pred p, q;\nsetp.ge.s32 p, %1, 60;\nsetp.lt.s32 q, %1, 32;\nselp.b32 %0, %3, %4, q;\nselp.b32 %0, %2, %0, p;\n}"
      : "=r"(wish) : "r"(tpc), "r"(4 + (tpc & 3)), "r"((tpc >> 3) + 8 * (tpc & 7)), "r"(12 + j7 + 8 * (tpc - 32 - 7 * j7)));
#define GET_ROLE()                                                                                   \
    mbar_wait(sb + BAR_RL, 0);                                                                       \
    uint32_t m0_, m1_;                                                                               \
    lds64(sb + OFF_RL, m0_, m1_);                                                                    \
    const int role = __shfl_sync(~0u, m0_ & 63, 0), r = 2 * (role >> 3) + rank, c = role & 7;        \
    const bool redo = __any_sync(~0u, m0_ != m1_);                                                   \
    if (!redo && role != wish) __trap();
#define XLOAD(wg, r, bar) _Pragma("unroll") for (int u = 0; u < 7; u++)                                                   \
    tma2d_e(sb + (u < 6 ? OFF_L + wg * kLBytes + u * 8192 : OFF_X6 + wg * 8192), &tm_x, 64 * u, (r) * 128 + wg * 64, bar)
#define XEXP(wg) if (lane < 4) { mbar_expect(sb + BAR_XF + 32 * wg + 8 * lane, lane < 3 ? 16384 : 8192); mbar_arrive(sb + BAR_XF + 32 * wg + 8 * lane); }
  uint32_t taken = 0;
  if (warp == 0) {
    asm volatile("{\n.reg .pred p;\nelect.sync _|p, -1;\n@p mbarrier.init.shared::cta.b64 [%0], 2;\n@p mbarrier.init.shared::cta.b64 [%0+8], 2;\n"
                 "@p mbarrier.init.shared::cta.b64 [%0+16], 2;\n@p mbarrier.init.shared::cta.b64 [%0+24], 2;\n"
                 "@p mbarrier.init.shared::cta.b64 [%0+-96], 1;\n@p mbarrier.init.shared::cta.b64 [%0+-88], 1;\n"
                 "fence.mbarrier_init.release.cluster;\nbarrier.cluster.arrive.relaxed.aligned;\n}" ::"r"(sb + BAR_XF) : "memory");
    XLOAD(0, 2 * (wish >> 3) + rank, sb + BAR_XF + 8 * (u >> 1));
    XEXP(0)
    __syncwarp();
  }
  if (warp == 1) {
    asm volatile("barrier.cluster.arrive.relaxed.aligned;" ::: "memory");
    if (lane + rank == 0) taken = atomicExch(&gs->claim[wish], 1u);
    __syncwarp();
  }
  if (warp > 1) {
    if (elect()) {
      if (warp == 11) asm volatile("prefetch.tensormap [%0];" ::"l"(&tm_qkv) : "memory");
      const int sh = 8 * (warp & 3);
      mbar_init(sb + OFF_BAR + 8 * warp, warp < 6 ? 1 : 4);
      mbar_init(sb + OFF_BAR + (warp < 4 ? 176 : 96) + 8 * warp, warp < 8 ? 1 + (warp >> 2) : (0x10400404 >> sh) & 255);
      mbar_init(sb + BAR_KV + sh, (0x04046002 >> sh) & 255);
      asm volatile("fence.mbarrier_init.release.cluster;" ::: "memory");
    }
    __syncwarp();
    asm volatile("barrier.cluster.arrive.relaxed.aligned;" ::: "memory");
  }

  if (warp < 8) {
    const int wg = warp >> 2;
    asm volatile("setmaxnreg.inc.sync.aligned.u32 232;");
    const uint32_t tsa = (warp & 3) ? 0u : sb + OFF_TS + wg * 184; (void)tsa;
    TS(0); TF(17);
    Ring rg{sb, (tid & 127) < 2 ? mapa(sb + BAR_EMPTY, tid & 1) : 0u};
    uint32_t A[112];
    float d0[28], d1[28];
    uint32_t xr[14], lsb = 0;
    float m0, e0, m1, e1;
    asm volatile("barrier.cluster.wait.aligned;" ::: "memory");
    if (warp == 1) {
      uint32_t m = wish;
#pragma unroll 1
      for (int n = 0; __any_sync(~0u, taken); n++) {
        if (n == 64) __trap();
        delay<1500>();
        uint32_t f0, f1;
        ld64((const uint2*)gs->claim + lane, f0, f1);
        const uint32_t z0 = __ballot_sync(~0u, !f0), z1 = __ballot_sync(~0u, !f1);
        m = (z0 ? 2 * __ffs(z0) - 2 : 2 * __ffs(z1) - 1) & 63;
        if (lane == 0) taken = atomicExch(&gs->claim[m], 1u);
        m += 64;
      }
      if (lane == 0) mbar_expect(sb + BAR_RL, 8);
      if (lane < 2)
        asm volatile("st.async.weak.shared::cluster.mbarrier::complete_tx::bytes.b32 [%0], %1, [%2];" ::"r"(mapa(sb + OFF_RL + 4 * rank, lane)), "r"(m), "r"(mapa(sb + BAR_RL, lane)) : "memory");
    }
    __syncwarp();
    GET_ROLE()
    if (redo) mbar_wait(sb + BAR_RD, 0);
    uint32_t epoch = ld32(&gs->epoch + (tid & zero));
    {
      const Half* gx = gs->pr[r].g[wg].ag[0];
      uint32_t* sw = (uint32_t*)(gx[c].b + kUnit) + (tid & 127);
      st32(sw, 0u);
      const uint32_t mhi = (uint32_t)(lane >> 4), l7 = (uint32_t)(lane & 7), ro = (uint32_t)((warp & 3) * 16 + (lane & 15)) * 128;
      const uint32_t xl = sb + OFF_L + wg * kLBytes + ro, x6 = sb + OFF_X6 + wg * 8192 + ro, xf = sb + BAR_XF + 32 * wg;
      mbar_wait_c(xf + 8 * ((7 * c) >> 4), 0);
      mbar_wait_c(xf + 8 * ((7 * c + 6) >> 4), 0);
      if (TSS == 8) TS(36);
#pragma unroll
      for (int j = 0; j < 7; j += 2) {
        uint32_t b = 7 * c + j + (j < 6 ? mhi : 0u);
        uint32_t a = (b < 48 ? xl + (b >> 3) * 8192 : x6) + (((b & 7) ^ l7) << 4);
        if (j < 6) ldsm4(a, xr[2 * j], xr[2 * j + 1], xr[2 * j + 2], xr[2 * j + 3]);
        else ldsm2(a, xr[12], xr[13]);
      }
      {
        float s0 = 0.f, s1 = 0.f, q0 = 0.f, q1 = 0.f;
#pragma unroll
        for (int j = 0; j < 7; j++) {
          const float a = blo(xr[2 * j]), b = bhi(xr[2 * j]), e = blo(xr[2 * j + 1]), f = bhi(xr[2 * j + 1]);
          s0 += a + b; s1 += e + f;
          q0 = fmaf(a, a, fmaf(b, b, q0));
          q1 = fmaf(e, e, fmaf(f, f, q1));
        }
        st32(sw, __float_as_uint(quad_stat(s0, s1, q0, q1, tid & 3)) | 1u);
      }
      if (TSS == 0 || TSS == 8) TS(40);
      TF(18);
      if (TSS == 8) { mbar_wait_c(xf, 0); TS(41); mbar_wait_c(xf + 8, 0); TS(42); mbar_wait_c(xf + 16, 0); TS(43); mbar_wait_c(xf + 24, 0); TS(44); }
      ldx_box<0>(A, xl, x6, xf, mhi, l7);
      if (TSS == 8) TS(45);
      ldx_box<1>(A, xl, x6, xf, mhi, l7);
      rg.acquire(0, 0);
      TS(2); TF(19);
      uint32_t sv[8];
      WG_FENCE; box_mma<0>(d0, A, sdesc(0)); WG_COMMIT;
      ldx_box<2>(A, xl, x6, xf, mhi, l7);
      WG_FENCE; box_mma<1>(d0, A, sdesc(0) + kBoxD); WG_COMMIT;
      if (TSS == 0) TS(41);
      ldx_box<3>(A, xl, x6, xf, mhi, l7);
#pragma unroll
      for (int i = 0; i < 8; i++) sv[i] = ld32((const uint32_t*)(gx[i].b + kUnit) + (tid & 127));
      rg.acquire(1, 0);
      WG_FENCE; box_mma<2>(d0, A, sdesc(1)); WG_COMMIT;
      if (TSS == 0) TS(42);
      TF(20);
      if (TSS == 0) TS(43);
      WG_FENCE; box_mma<3>(d0, A, sdesc(1) + kBoxD); WG_COMMIT;
      if (lane < 2) mbar_arrive_cl(mapa(sb + BAR_XIN, lane));
      TS(1);
      TF(0);
      TSG(62);
      row_stats<true>(sv, 0.f, 1u, gx, c, tid, m0, e0, m1, e1);
      epoch = __shfl_sync(~0u, epoch, 0);
      st32(sw + 8 * kSlot / 4, 0u);
#pragma unroll
      for (int i = 0; i < 2; i++) st128(&gs->kv1[c][(tid & 127) >> 3][r][wg * 16 + i * 8 + (tid & 7)], 0u, 0u, 0u, 0u);
    }
    const int r_ = r, c_ = c, wg_ = wg;

#pragma unroll 1
    for (int layer = 0;; layer++) {
#define DERIVE(k)                                                                                                                    \
      const int zz = (layer + k) & zero;                                                                                             \
      const int r = r_ + zz, c = c_ + zz, wg = wg_ + zz, tid = threadIdx.x + zz, lane = tid & 31, t = tid & 3, c1 = c & ~1;          \
      const uint32_t lz = sb + OFF_L + wg * kLBytes;                                                                                 \
      Xa xa;                                                                                                                         \
      xa.o16 = (warp & 3) * 1792 + lane * 16; xa.l16 = lz + xa.o16; xa.o8 = (warp & 3) * 1792 + 1536 + lane * 8; xa.l8 = lz + xa.o8; \
      xa.xf = sb + BAR_XF + 32 * wg; xa.lane = lane; xa.tsa = layer == 1 && TSS ? tsa : 0u;                                      \
      Grp* G = &gs->pr[r].g[wg];                                                                                                 \
      Flg* F = &gs->pr[r].f[wg];                                                                                                 \
      const uint32_t tag = epoch * 8 + 1 + 4 * layer + zz, P = (layer ^ 1) + zz;                                                     \
      const bool isB = lane >= 16;                                                                                                   \
      const uint32_t l7 = (uint32_t)(tid & 7), mrow = (uint32_t)((warp & 3) * 16 + (tid & 15)), mhi = (uint32_t)(lane >> 4);         \
      (void)t; (void)c1; (void)G; (void)F; (void)tag; (void)P; (void)isB; (void)l7; (void)mrow; (void)mhi;
      const int tsb = 2 + layer * 18; (void)tsb;
      float L0, L1;
      uint32_t s0, s1, b0, b1, T[14];
      float stat;
      {
        DERIVE(0)
        mbar_wait_c(sb + BAR_CS, 0);
        uint32_t cs[14];
#pragma unroll
        for (int i = 0; i < 7; i++) lds64(sb + OFF_CSK + t * 8 + i * 32, cs[2 * i], cs[2 * i + 1]);
        TSV(tsb + 1);
        const float rs0 = rsq(fmaxf(fmaf(-m0, m0, e0), 0.f) + 1e-5f), rs1 = rsq(fmaxf(fmaf(-m1, m1, e1), 0.f) + 1e-5f);
        s0 = pack(0.5f * rs0, 0.5f * rs0); s1 = pack(0.5f * rs1, 0.5f * rs1);
        const float f0 = blo(s0), f1 = blo(s1), o0 = -m0 * f0, o1 = -m1 * f1;
        b0 = pack(o0, o0); b1 = pack(o1, o1);
        L0 = 1.4426950408889634f * rs0 * rcp(f0);
        L1 = 1.4426950408889634f * rs1 * rcp(f1);
#pragma unroll
        for (int i = 0; i < 7; i++) {
          d1[4 * i] = o0 * __uint_as_float(cs[2 * i]); d1[4 * i + 1] = o0 * __uint_as_float(cs[2 * i + 1]);
          d1[4 * i + 2] = o1 * __uint_as_float(cs[2 * i]); d1[4 * i + 3] = o1 * __uint_as_float(cs[2 * i + 1]);
        }
        SCHED_FENCE();
        WG_WAIT(0);
        rg.release(0); rg.release(1);
#pragma unroll
        for (int i = 0; i < 28; i++) d0[i] = fmaf(d0[i], (i & 2) ? f1 : f0, d1[i]);
      }
      TSV(tsb + 2); TF(1 + 8 * layer + 0);
      phi_proj(d1, d0, dzs.z[0]);
      SCHED_FENCE();
      nm_box<0>(A, s0, s1, b0, b1);
      nm_box<1>(A, s0, s1, b0, b1);
      {
        DERIVE(6)
        sts14(xr, 6, xa);
        if (layer == 0) { const uint32_t z[14] = {}; stg14(&G->pb[(c + 6) & 7][1], z, xa); }
      }
      SCHED_FENCE();
      WG_WAIT(0);
      GIVE(8, wg_);
#pragma unroll 1
      for (int pass = layer & zero;; pass++) {
        DERIVE(pass + 1)
        dz = dzs.z[1];
        float e[28];
        uint32_t o[16];
        const uint32_t pa = lz + pass * 24576 + mrow * 128;
        sm_a(d1, e, L0, L1);
        if (pass == 0) {
          TAKE(8, !wg);
          rg.acquire_s(2, 0);
          WG_FENCE; box_mma<0>(d0, A, sdesc(2)); box_mma<1>(d0, A, sdesc(2) + kBoxD); WG_COMMIT;
          nm_box<2>(A, s0, s1, b0, b1); nm_box<3>(A, s0, s1, b0, b1);
        }
        sm_b(d1, e, o, pa, mhi, l7);
        if (pass == 0) {
          rg.acquire_s(3, 0);
          drain(rg, 2);
          WG_FENCE; box_mma<2>(d0, A, sdesc(3)); box_mma<3>(d0, A, sdesc(3) + kBoxD); WG_COMMIT;
        }
        sm_c(d1, o, pa, mhi, l7);
        WG_WAIT(0);
        if (pass) break;
        rg.release(3);
        {
          const uint32_t vb = pa + 16384;
#pragma unroll
          for (int j = 0; j < 6; j += 2)
            stsm4(vb + (((j + mhi) ^ l7) << 4), pack(d0[4 * j], d0[4 * j + 1]), pack(d0[4 * j + 2], d0[4 * j + 3]), pack(d0[4 * j + 4], d0[4 * j + 5]), pack(d0[4 * j + 6], d0[4 * j + 7]));
          stsm4(vb + (((6 + mhi) ^ l7) << 4), pack(d0[24], d0[25]), pack(d0[26], d0[27]), 0x3F803F80u, 0x3F803F80u);
        }
        FENCE_ASYNC;
        TSV(tsb + 3);
        {
          const Desc db = mkdesc(OFF_L) + 1024;
          if (wg == 0) {
            asm volatile("bar.sync 6, 128;" ::: "memory");
            float e[32], f[32];
            WG_FENCE;
#pragma unroll
            for (int k = 0; k < 4; k++) { wgmma_ss_n64(e, mkdesc(OFF_L) + k * 128, db + k * 128, k != 0); wgmma_ss_n64(f, mkdesc(OFF_L) + 512 + k * 128, db + k * 128, k != 0); }
            WG_COMMIT;
            asm volatile("bar.sync 2, 256;" ::: "memory");
            WG_FENCE;
#pragma unroll
            for (int k = 0; k < 4; k++) wgmma_ss_n64(e, mkdesc(OFF_L + kLBytes) + k * 128, db + (kLBytes >> 4) + k * 128, true);
            WG_COMMIT;
#pragma unroll
            for (int k = 0; k < 4; k++) wgmma_ss_n64(f, mkdesc(OFF_L + kLBytes) + 512 + k * 128, db + (kLBytes >> 4) + k * 128, true);
            WG_COMMIT;
            uint4* p1 = &gs->kv1[c][(tid & 127) >> 3][r][tid & 7];
            WG_WAIT(1);
            send_kv(p1, e, isB, t, P);
            SCHED_FENCE();
            WG_WAIT(0);
            send_kv(p1 + 16, f, isB, t, P);
            if (tid == 0) { mbar_arrive(sb + BAR_KV); mbar_arrive(sb + BAR_KV); }
          } else {
            asm volatile("bar.arrive 2, 256;" ::: "memory");
            delay<QD>();
          }
          rg.acquire(0, P);
          WG_FENCE; box_mma<0>(d0, A, sdesc(0));
        }
        TSV(tsb + 4); TF(1 + 8 * layer + 1);
        rg.acquire(1, P);
        WG_FENCE; box_mma<1>(d0, A, sdesc(0) + kBoxD); box_mma<2>(d0, A, sdesc(1)); box_mma<3>(d0, A, sdesc(1) + kBoxD); WG_COMMIT;
        WG_WAIT(0);
        rg.release(0); rg.release(1);
        phi_proj(d1, d0, dz);
        WG_WAIT(0);
      }
      TSV(tsb + 5);
      {
      DERIVE(3)
      dz = dzs.z[2];
      lds14(xr, xr[12], xr[13], 6, xa);
      {
        FENCE_ASYNC;
        asm volatile("bar.sync %0, 128;" ::"r"(6 + wg) : "memory");
        float d[32];
        uint32_t R[14];
        const Desc dq{dz + wg * (kLBytes >> 4), (1024 + OFF_L + 24576) >> 4};
        if (TSS != 3) TS(38);
        mbar_wait_c(sb + BAR_KV + 8, layer);
        TS(39);
        TAKE(5, wg);
        WG_FENCE;
#pragma unroll
        for (int k = 0; k < 7; k++) wgmma_sk_n64(d, dq + (k >> 2) * 512 + (k & 3) * 2, mkdesc(OFF_KVS) + k * 128, k != 0);
        WG_COMMIT;
        WG_WAIT(0);
        const bool lo = t < 2;
        const float m0 = rcp(fmaf(lo ? d[17] : d[13], 0.5f, 0.5e-6f)), m1 = rcp(fmaf(lo ? d[19] : d[15], 0.5f, 0.5e-6f));
        const float n0 = __shfl_xor_sync(~0u, m0, 2), n1 = __shfl_xor_sync(~0u, m1, 2);
        const float ia0 = lo ? n0 : m0, ib0 = lo ? m0 : n0, ia1 = lo ? n1 : m1, ib1 = lo ? m1 : n1;
#pragma unroll
        for (int j = 0; j < 3; j++) {
          R[2 * j] = pack(d[4 * j] * ia0, d[4 * j + 1] * ia0);
          R[2 * j + 1] = pack(d[4 * j + 2] * ia1, d[4 * j + 3] * ia1);
          R[2 * j + 8] = pack(d[4 * j + 20] * ib0, d[4 * j + 21] * ib0);
          R[2 * j + 9] = pack(d[4 * j + 22] * ib1, d[4 * j + 23] * ib1);
        }
        R[6] = pack((lo ? d[12] : d[16]) * n0, (lo ? d[13] : d[17]) * n0);
        R[7] = pack((lo ? d[14] : d[18]) * n1, (lo ? d[15] : d[19]) * n1);
        TSV(tsb + 6); TF(1 + 8 * layer + 2);
        const uint32_t Po = ((epoch & 1) ^ 1) + zz;
        mark14(R, Po);
        stg14(&G->ag[0][c], R, xa);
        hint(&F->fl[1][4 * c + (warp & 3)], tag, xa);
        own_to_A(A, R);
        const Half* gx = G->ag[0];
        pull<0, DO, false>(gx, F->fl[1], tag, c, warp & 3, wg, lz, xa);
        GIVE(5, !wg);
        TSV(tsb + 7);
        if (layer == 0 && wg == 1) {
          float q[4];
          rg.acquire2(0, 0);
          colsum(q, sdesc(0));
          WG_WAIT(0);
          put_cs(q, sb + OFF_CS, sb + BAR_CS + 8, warp, lane);
        }
#pragma unroll
        for (int i = 0; i < 14; i++) { d0[2 * i] = blo(xr[i]); d0[2 * i + 1] = bhi(xr[i]); }
        rg.acquire2(2, 1);
        WG_FENCE; box_mma<0, 0, 3, true>(d0, A, sdesc(2));
        front<false>(d0, A, sdesc(2), sdesc(3), rg, 2, 1, Po, Po, gx, c, tid, lz, xa, TSS == 1 ? 40 : 0, 0.f, e0, e0, e1, e1);
        WG_WAIT(0);
      }
      }
      TSV(tsb + 8); TF(1 + 8 * layer + 3);
      {
      DERIVE(5)
      dz = dzs.z[3];
      publish(A, xr, stat, d0, &G->ag[1][c], F->fl[2], c, tag + 1, P, P, tid, xa);
      {
        Half* hme = G->hx[c];
        uint32_t* fpeer = &F->fh[c ^ 1][warp & 3];
        {
          const Half* gx = G->ag[1];
          pull<10, DX1>(gx, F->fl[2], tag + 1, c, warp & 3, wg, lz, xa);
          rg.acquire2(0, layer);
          TSV(tsb + 9);
          WG_FENCE; box_mma<0, 0, 3>(d1, A, sdesc(0));
          lsb = (xr[0] & 1) + 2 * (xr[4] & 1) + 4 * (xr[8] & 1) + 8 * (xr[12] & 1);
          front<true>(d1, A, sdesc(0), sdesc(1), rg, 0, 0, P, P, gx, c, tid, lz, xa, TSS == 3 ? 40 : 0, stat, m0, e0, m1, e1);
          WG_WAIT(1);
          rg.release(4 + wg); rg.release(4 + wg);
          TSV(tsb + 10);
          const float hs0 = 0.5f * rsq(fmaxf(fmaf(-m0, m0, e0), 0.f) + 1e-5f), hs1 = 0.5f * rsq(fmaxf(fmaf(-m1, m1, e1), 0.f) + 1e-5f);
          s0 = pack(hs0, hs0); s1 = pack(hs1, hs1);
          const float o0 = -m0 * blo(s0), o1 = -m1 * blo(s1);
          b0 = pack(o0, o0); b1 = pack(o1, o1);
          nm_box<0>(A, s0, s1, b0, b1);
          TSV(tsb + 11); TF(1 + 8 * layer + 4);
          stage_a<0>(d0, A, rg, 2, sdesc(2), 0, 1);
          nm_box<1>(A, s0, s1, b0, b1);
          stage_b<0>(d0, A, sdesc(2));
          nm_box<2>(A, s0, s1, b0, b1);
          mbar_wait_c(sb + BAR_CS + 8, 0);
          fold_ln(d1, sb + OFF_CS + t * 8, hs0, hs1, -hs0 * m0, -hs1 * m1);
          glu_gate<0, 7>(T, d1);
          stage_a<1>(d0, A, rg, 4, mkdesc(OFF_E), layer, 2);
#pragma unroll
          for (int i = 14; i < 28; i++) asm volatile("" : "+f"(d1[i]));
          nm_box<3>(A, s0, s1, b0, b1);
          glu_gate<7, 14>(T, d1);
          stage_b<1, false>(d0, A, mkdesc(OFF_E));
        }
#pragma unroll 1
        for (int j = zz; j < 3; j++) {
          const uint32_t sl = j == 0 ? 0x41503u : j == 1 ? 0x10342u : 0x03215u, ph = (layer ? 0x2D4u : 0x17Au) >> 4 * j;
          const int s0 = sl & 7, s1 = (sl >> 4) & 7, s2 = (sl >> 8) & 7, s3 = (sl >> 12) & 7;
          stage<0>(d1, A, rg, s0, ddesc(s0), ph & 1, sl >> 16);
          {
            uint32_t h[14];
            glu_up(h, T, d0);
            mark14(h, P);
#pragma unroll
            for (int i = 0; i < 14; i++) asm volatile("" : "+r"(h[i]));
            stage_a<1>(d1, A, rg, s1, ddesc(s1), (ph >> 1) & 1, s0);
            send14(hme + j, fpeer + 4 * j, tag + 2, h, xa);
            sts14(h, j, xa);
            stage_b<1, false>(d1, A, ddesc(s1));
          }
          stage<0>(d0, A, rg, s2, ddesc(s2), (ph >> 2) & 1, s1);
          glu_gate<0, 7>(T, d1);
          stage_a<1>(d0, A, rg, s3, Desc{dz + s3 * (kStageBytes >> 4), 64}, (ph >> 3) & 1, s2);
#pragma unroll
          for (int i = 14; i < 28; i++) asm volatile("" : "+f"(d1[i]));
          glu_gate<7, 14>(T, d1);
          stage_b<1, false>(d0, A, Desc{dz + s3 * (kStageBytes >> 4), 64});
        }
        TSV(tsb + 12); TF(1 + 8 * layer + 5);
      }
      }
      DERIVE(4)
      dz = dzs.z[4];
      {
        Half* hme = G->hx[c];
        uint32_t* fpeer = &F->fh[c ^ 1][warp & 3];
        lds14(&A[0], A[24], A[25], 0, xa);
        lds14(&A[12], A[26], A[27], 1, xa);
        stage_a<0>(d1, A, rg, 0, sdesc(0), P, 3);
        lds14(&A[28], A[52], A[53], 2, xa);
        {
          uint32_t h[14];
          glu_up(h, T, d0);
          mark14(h, P);
          stg14(hme + 3, h, xa);
          hint(fpeer + 12, tag + 2, xa);
#pragma unroll
          for (int i = 0; i < 12; i++) A[40 + i] = h[i];
          A[54] = h[12]; A[55] = h[13];
        }
        TSV(tsb + 13);
        Half* pout = &G->pb[0][0];
        uint32_t* fout = &F->fh[0][16 + (warp & 3)];
        const Half* gh = &G->hx[0][0] + (c ^ 1) * 4 - 4;
        stage_b<0>(d1, A, sdesc(0));
        if (lane == 0) mbar_arrive(sb + BAR_LFREE + 8 * wg);
        ld_box<2>(A, 1, xa);
        stage<0>(d0, A, rg, 1, sdesc(1), P, 0);
        ck_box<2>(A, P, gh, 0, xa);
        stage_a<1>(d1, A, rg, 2, sdesc(2), 1, 1);
        ld_box<3>(A, 1, xa);
        ck_box<3>(A, P, gh, 0, xa);
        TSV(tsb + 14);
        TAKE(3, wg);
        stage_b<1, false>(d1, A, sdesc(2));
        stage_a<1>(d0, A, rg, 3, sdesc(3), 1, -1);
        rg.release(4 + wg); rg.release(4 + wg);
        if (layer) rg.ebar = 0;
        send_acc(pout + ((c + 2) & 7) * 4 + 2, fout + ((c + 2) & 7) * 32 + 8, tag + 2, d1, P, xa);
        stage_b<1, false>(d0, A, sdesc(3));
        float d2[28];
        dz = dzs.z[5];
        stage_a<0>(d2, A, rg, 0, sdesc(0), layer, -1);
        send_acc(pout + ((c + 4) & 7) * 4 + 3, fout + ((c + 4) & 7) * 32 + 12, tag + 2, d0, P, xa);
        stage_b<0, false>(d2, A, sdesc(0));
        GIVE(3, !wg);
        ldg14(xr, &G->ag[1][c], xa);
        stage_a<1>(d2, A, rg, 1, sdesc(1), layer, 0);
        GIVE(4, wg);
        stage_b<1>(d2, A, sdesc(1));
#pragma unroll
        for (int i = 0; i < 4; i++) xr[4 * i] = (xr[4 * i] & ~1u) | ((lsb >> i) & 1);
#pragma unroll
        for (int i = 0; i < 14; i++) { d0[2 * i] = blo(xr[i]); d0[2 * i + 1] = bhi(xr[i]); }
        PIN28(d0);
        SCHED_FENCE();
        drain(rg, 1);
        send_acc<false>(pout + ((c + 6) & 7) * 4 + 1, fout + ((c + 6) & 7) * 32 + 4, tag + 2, d2, P, xa);
        TAKE(4, !wg);
        stage_a<0, true>(d0, A, rg, 4, mkdesc(OFF_E), layer, -1);
        stage_b<0, false>(d0, A, mkdesc(OFF_E));
        stage<1>(d0, A, rg, 5, mkdesc(OFF_E + kLBytes), layer, 4);
        TSV(tsb + 15); TF(1 + 8 * layer + 6);
        {
          uint32_t R[14];
          ldg14(R, &G->pb[c][1], xa);
#pragma unroll
          for (int i = 0; i < 12; i++) A[12 + i] = R[i];
          A[26] = R[12]; A[27] = R[13];
        }
        ld_box<1>(A, 1, xa);
        ck_box<1>(A, P, G->pb[c], 0, xa);
        asm volatile("bar.sync %0, 128;" ::"r"(6 + wg) : "memory");
#pragma unroll
        for (int e = 0; e < 14; e++) {
          const uint32_t p1 = A[e < 12 ? 28 + e : 40 + e], p2 = A[e < 12 ? 40 + e : 42 + e];
          d1[2 * e] = blo(p1) + blo(p2);
          d1[2 * e + 1] = bhi(p1) + bhi(p2);
        }
        PIN28(d1);
        SCHED_FENCE();
        drain(rg, 5);
#pragma unroll
        for (int e = 0; e < 28; e++) d0[e] += d1[e];
        PIN28(d0);
        SCHED_FENCE();
        ck_box<0>(A, P, G->pb[c], 0, xa);
#pragma unroll
        for (int e = 0; e < 14; e++) {
          const uint32_t p0 = A[e < 12 ? 12 + e : 14 + e];
          d0[2 * e] += blo(p0);
          d0[2 * e + 1] += bhi(p0);
        }
      }
      if (layer) {
        uint4* o0 = (uint4*)(out + (size_t)(r * 128 + warp * 16 + (lane >> 2)) * 448 + c * 56) + t;
#pragma unroll
        for (int g = 0; g < 4; g++) {
          uint32_t v[4];
#pragma unroll
          for (int i = 0; i < 4; i++) {
            const int x = 16 * (g >> 1) + 4 * i + 2 * (g & 1);
            v[i] = x < 28 ? pack(d0[x < 28 ? x : 0], d0[x < 28 ? x + 1 : 0]) : 0u;
          }
          quad_tr(v, t);
          if (g < 2 || t < 3) o0[(g & 1) * 448 + 4 * (g >> 1)] = make_uint4(v[0], v[1], v[2], v[3]);
        }
        break;
      }
      TSV(tsb + 17); TF(8);
      {
        const Half* gx = G->ag[0];
        const uint32_t Px = epoch & 1;
        dz = dzs.z[6];
        publish(A, xr, stat, d0, &G->ag[0][c], F->fl[0], c, tag + 3, Px, 0u, tid, xa);
        xa.tsa = tsa;
        mbar_wait_c(sb + BAR_EMPTY + 8 * (4 + wg), 0);
        pull<10, DX2>(gx, F->fl[0], tag + 3, c, warp & 3, wg, lz, xa);
        rg.acquire2(0, 1);
        TS(20);
        WG_FENCE; box_mma<0, 0, 3>(d0, A, sdesc(0));
        front<true>(d0, A, sdesc(0), sdesc(1), rg, -1, 0, Px, 0u, gx, c, tid, lz, xa, TSS == 2 ? 40 : 0, stat, m0, e0, m1, e1);
      }
    }
    if (r_ + c_ + tid == 0) gs->epoch = epoch + 1;
    TS(37); TF(16);
    TSG(63);
  } else {
    asm volatile("setmaxnreg.dec.sync.aligned.u32 40;");
    __syncwarp();
    const uint32_t ep = ld32(&gs->epoch + (tid & zero));
    uint2 wpv[7] = {};
#define WPLOAD(c) if (warp > 9 && (tid & 7) < 7) {                                               \
      const uint2* wp = (const uint2*)w_phi + (((c) * 56 + ((tid >> 3) & 7)) * 7 + (tid & 7));   \
      _Pragma("unroll") for (int i = 0; i < 7; i++) ld64(wp + i * 56, wpv[i].x, wpv[i].y);       \
    }
    WPLOAD(wish & 7)
    __syncwarp();
    asm volatile("barrier.cluster.wait.aligned;" ::: "memory");
    if (warp == 8) {
      const uint32_t kd = sb + rank * kBoxBytes, kc = 448 + 56 * (wish & 7);
      tma2d_mce(kd, &tm_qkv, kc, 112 * rank, sb + BAR_FULL);
      tma2d_mce(kd + kUnit, &tm_qkv, kc, 112 * rank + 56, sb + BAR_FULL);
      XLOAD(1, 2 * (wish >> 3) + rank, sb + BAR_XF + 32 + 8 * (u >> 1));
      tma2d_mce(kd + kStageBytes, &tm_qkv, kc, 112 * rank + 224, sb + BAR_FULL + 8);
      tma2d_mce(kd + kStageBytes + kUnit, &tm_qkv, kc, 112 * rank + 280, sb + BAR_FULL + 8);
      XEXP(1)
      if (lane < 2) mbar_expect(sb + BAR_FULL + 8 * lane, 4 * 6272);
    }
    __syncwarp();
    GET_ROLE()
    if (redo) {
      if (warp == 8) {
#pragma unroll 1
        for (int i = 0; i < 10; i++) mbar_wait(sb + (i < 2 ? BAR_FULL : BAR_XF - 16) + 8 * i, 0);
        if (lane == 0) mbar_expect(sb + BAR_RD, 14 * 8192 + 8 * 6272);
#pragma unroll 1
        for (int u = 0; u < 14; u++) tma2d_e(sb + (u < 12 ? OFF_L + (u & 1) * kLBytes + (u >> 1) * 8192 : OFF_X6 + (u & 1) * 8192), &tm_x, 64 * (u >> 1), r * 128 + (u & 1) * 64, sb + BAR_RD);
#pragma unroll 1
        for (int u = 0; u < 8; u++) tma2d_e(sb + u * kUnit, &tm_qkv, 448 + 56 * c, 56 * u, sb + BAR_RD);
      }
      WPLOAD(c)
      mbar_wait(sb + BAR_RD, 0);
    }
    __syncwarp();
    if (sb != (uint32_t)__cvta_generic_to_shared(smem)) __trap();
    const int pid = 2 * role + rank;
    if (tid == 256) { delay<PFD>(); prefetch_l2(w_qkv + pid * 4704, 9408); }
    __syncwarp();
    if (warp == 9) {
      const uint32_t i = lane >> 1;
      const uint32_t o = i < 3 ? i * 32 + 4 * c : i < 7 ? 84 + (c ^ 1) * 32 + 4 * i : 112 + ((c + 2 * i + 2) & 7) * 32 + 4 * ((0x1320u << 2 >> 4 * i - 26) & 3);
      if (i < 11) st128(&gs->pr[r].f[lane & 1].fl[0][0] + o, 0u, 0u, 0u, 0u);
      st128(&gs->kv2[c][(lane & 16) * 4 + (r >> 2) * 16 + (lane & 8) + (r & 3) * 2][lane & 7], 0u, 0u, 0u, 0u);
    } else if (warp > 9) {
      const uint32_t k0 = (tid >> 3) & 7, j = tid & 7, wa = sb + OFF_WP + k0 * 128 + ((j ^ k0) << 4);
      sts128(wa + 7168, 0u, 0u, 0u, 0u);
#pragma unroll
      for (int i = 0; i < 7; i++) {
        const bool hb = i > 3 || (i == 3 && k0 > 3);
        sts128(wa + i * 1024, hb ? 0u : wpv[i].x, hb ? 0u : wpv[i].y, hb ? wpv[i].x : 0u, hb ? wpv[i].y : 0u);
      }
      if (tid < 328) sts128(sb + OFF_ONES + (tid - 320) * 16, 0x3F803F80u, 0x3F803F80u, 0x3F803F80u, 0x3F803F80u);
      FENCE_ASYNC;
      mbar_arrive(sb + BAR_WP);
    }
    __syncwarp();
    {
      float q[4];
      mbar_wait(sb + BAR_WP, 0);
      mbar_wait(sb + BAR_FULL, 0);
      dz = dzs.z[7];
      colsum<0, 14>(q, sdesc(0));
      mbar_wait(sb + BAR_FULL + 8, 0);
      if (warp == 8 && elect()) {
        mbar_expect(sb + BAR_FULL + 16, 4 * 6272);
        tma2d_mc(sb + 2 * kStageBytes + rank * kBoxBytes, &tm_qkv, 896 + 56 * c, 112 * rank, sb + BAR_FULL + 16);
        tma2d_mc(sb + 2 * kStageBytes + rank * kBoxBytes + kUnit, &tm_qkv, 896 + 56 * c, 112 * rank + 56, sb + BAR_FULL + 16);
      }
      __syncwarp();
      colsum<14>(q, sdesc(0));
      WG_WAIT(0);
      put_cs(q, sb + OFF_CSK, sb + BAR_CS, warp, lane);
      if (elect()) asm volatile("prefetch.tensormap [%0];" ::"l"(&tm.m[warp - 6]) : "memory");
      if (tid == 288) {
        prefetch_l2(w_d + pid * 6272, 12544);
        prefetch_l2(w_o + pid * 1568, 3136);
        prefetch_l2(w_g + pid * 6272, 12544);
        prefetch_l2(w_u + pid * 6272, 12544);
      }
      __syncwarp();
    }
    if (warp == 8) {
      uint32_t t0, t1, t2, t3;
      {
        const int p = lane & 15;
        int mi;
        if (p < 12) {
          const int c0 = p < 4 ? (p < 2 ? 448 + 448 * p : 0) + 56 * c : 224 * c + 56 * ((p - 4) >> 1);
          mi = p < 3 ? 1 : p == 3 ? 2 : 3 + (p & 1);
          const int ka = lane > 15 ? 0 : rank ? c & ~1 : c, kb = lane > 15 ? 0 : c & ~1;
          t0 = c0 * 0x10001;
          t1 = 56 * (ka ^ (2 * rank)) + ((56 * (ka ^ (2 * rank + 1))) << 16);
          t2 = 56 * (kb ^ (2 * rank + 4)) + ((56 * (kb ^ (2 * rank + 5))) << 16);
        } else {
          const int q = p - 12;
          mi = 5;
          t0 = 64 * ((c + 2 + (q < 2 ? 0 : 2 * q)) & 7) + ((64 * ((c + 2 + (q < 2 ? 2 : 2 * q)) & 7)) << 16);
          t1 = (224 * (c ^ (q == 1)) + 112 * rank) * 0x10001 + (56 << 16);
          t2 = (224 * (c ^ (q != 0)) + 112 * rank) * 0x10001 + (56 << 16);
        }
        t3 = mi * 128 + ((uint32_t)(0x4020253253202020ull >> 4 * p) & 7) + (((uint32_t)(0x5131310410413131ull >> 4 * p) & 7) << 4) +
             (((0xCC73u >> p) & 1) << 16) + (((0xCF13u >> p) & 1) << 17);
      }
#pragma unroll 1
      for (int it = 1; it < 32; it++) {
        const int src = it < 3 ? 16 + it : it & 15;
        if (src == 4) {
          mbar_wait(sb + BAR_KV, it >> 4);
          kv_hop1(gs, c + (it & zero), r + (it & zero), 0, lane + (it & zero), it >> 4);
        }
        const uint32_t w0 = __shfl_sync(~0u, t0, src), w1 = __shfl_sync(~0u, t1, src), w2 = __shfl_sync(~0u, t2, src), w3 = __shfl_sync(~0u, t3, src);
        const CUtensorMap* m = (const CUtensorMap*)((const char*)&tm + (w3 & 0x380));
        const uint32_t sa = w3 & 7, sc = (w3 >> 4) & 7, par = ((w3 >> 16) & 1) ^ ((sa & 6) != 2 && it > 15), par2 = (w3 >> 17) ^ ((sc & 6) != 2 && it > 15), bar = sb + BAR_FULL + sa * 8, bar2 = sb + BAR_FULL + sc * 8;
        const uint32_t dst = sb + (sa < 4 ? sa * kStageBytes : OFF_E + (sa - 4) * kLBytes) + rank * kBoxBytes, dst2 = sb + (sc < 4 ? sc * kStageBytes : OFF_E + (sc - 4) * kLBytes) + rank * kBoxBytes;
#define REFILL(bar, par, dst, x, y0, y1) asm volatile("{\n.reg .pred p, q;\n.reg .b32 n;\nmov.b32 n, 0;\nLW:\nmbarrier.try_wait.parity.shared::cta.b64 p, [%2+48], %8;\n@p bra LD;\n" \
            "add.u32 n, n, 1;\nsetp.lt.u32 q, n, %9;\n@q bra LW;\ntrap;\nLD:\nelect.sync _|p, -1;\n"                                                   \
            "@p cp.async.bulk.tensor.2d.shared::cluster.global.mbarrier::complete_tx::bytes.multicast::cluster [%0], [%1, {%3,%4}], [%2], %6;\n"           \
            "@p cp.async.bulk.tensor.2d.shared::cluster.global.mbarrier::complete_tx::bytes.multicast::cluster [%7], [%1, {%3,%5}], [%2], %6;\n"           \
            "@p mbarrier.arrive.expect_tx.shared::cta.b64 _, [%2], 25088;\n}"                                                                              \
            ::"r"(dst), "l"(m), "r"(bar), "r"(x), "r"(y0), "r"(y1), "h"((uint16_t)3), "r"(dst + kUnit), "r"(par), "n"(kSpin) : "memory")
        if (it > 1) REFILL(bar, par, dst, w0 & 0xFFFF, w1 & 0xFFFF, w1 >> 16);
        else mbar_wait(sb + BAR_XIN, 0);
        REFILL(bar2, par2, dst2, w0 >> 16, w2 & 0xFFFF, w2 >> 16);
      }
    } else {
      const uint32_t epu = __shfl_sync(~0u, ep, 0);
      const int warp_ = warp, r_ = r, c_ = c;
      {
        const int g = (tid - 288) >> 3, j = tid & 7;
        const uint4* src = (const uint4*)w_d + pid * 784 + g * 7 + j;
        uint4* dst = wd + pid * 896 + tid - 288;
        mbar_wait(sb + BAR_XIN, 0);
#pragma unroll 1
        for (int k = 0; k < 10; k += 5) {
          uint4 v[5] = {};
#pragma unroll
          for (int i = 0; i < 5; i++) if (j < 7 && g + 12 * (k + i) < 112) v[i] = __ldg(src + 84 * (k + i));
#pragma unroll
          for (int i = 0; i < 5; i++) if (g + 12 * (k + i) < 112) dst[96 * (k + i)] = v[i];
        }
        asm volatile("bar.sync 1, 96;" ::: "memory");
      }
#pragma unroll 1
      for (uint32_t L = 0; L < 2; L++) {
        const int lane = (threadIdx.x + (L & zero)) & 31, warp = warp_ + (L & zero), r = r_ + (L & zero), c = c_ + (L & zero);
        mbar_wait(sb + BAR_KV, L);
#pragma unroll
        for (int i = 0; i < 5; i++) sts128(sb + OFF_KVS + (warp - 9 + 3 * i) * 1024 + (lane >> 2) * 128 + 64 + (lane & 3) * 16, 0u, 0u, 0u, 0u);
        kv_hop1(gs, c, r, warp - 8, lane, L);
        SCHED_FENCE();
        {
          const uint32_t P = L ^ 1;
          const uint4* p2 = &gs->kv2[c][0][0] + (warp - 9) * 32 + lane;
          const uint32_t kb = sb + OFF_KVS + (warp - 9) * 1024 + (lane >> 2) * 128 + ((((lane >> 2) & 3) ^ (lane & 3)) << 4);
          uint4 u[5] = {};
#pragma unroll
          for (int i = 0; i < 5; i++) u[i].y = (i < 4 || warp < 11) ? L : P;
#pragma unroll 1
          for (int n = 0; n < kSpin; n++) {
#pragma unroll
            for (int i = 0; i < 5; i++) ld128_if(p2 + i * 96, u[i], P);
            if (!__any_sync(~0u, (lop_7e(u[0].y, u[1].y, P) | lop_7e(u[2].y, u[3].y, P) | (u[4].y ^ P)) & 1)) break;
          }
#pragma unroll
          for (int i = 0; i < 5; i++) sts128(kb + i * 3072, u[i].x, u[i].y, u[i].z, u[i].w);
          FENCE_ASYNC;
          mbar_arrive(sb + BAR_KV + 8);
        }
        if (L && tid == 288 && !rank) st32(&gs->claim[role], 0u);
        SCHED_FENCE();
        if (warp > 9) {
          const int w = warp - 10;
          const Grp* G = &gs->pr[r].g[w];
          const Flg* F = &gs->pr[r].f[w];
          const uint32_t tag = epu * 8 + 3 + 4 * L;
          {
            const int j = lane ^ 4;
            const Half* src = lane < 4 ? &G->hx[c ^ 1][lane] : &G->pb[c][(lane - 4) & 3];
            const uint32_t bar = sb + BAR_XF + 32 * w + 8 * (j >> 1), dst = sb + OFF_L + w * kLBytes + (j - 1) * kSlot;
            mbar_wait(sb + BAR_EMPTY + 8 * (4 + w), L); mbar_wait(sb + BAR_EMPTY + 8 * (4 + w), L ^ 1); mbar_wait(sb + BAR_EMPTY + 8 * (4 + w), L);
            bool pend = j > 1 && j < 8;
            if (j < 2) mbar_arrive(bar);
#pragma unroll 1
            for (int n = 0; __any_sync(~0u, pend); n++) {
              const uint32_t ok = __ballot_sync(~0u, ld32(&F->fh[c][lane]) == tag);
              const bool fr = lane < 4 || mbar_test(sb + BAR_LFREE + 8 * w, L);
              if (pend && fr && (((ok >> (4 * lane & 31)) & 15) == 15 || n > kSpin)) {
                mbar_expect(bar, kUnit);
                bulk_g2s(dst, src, kUnit, bar);
                pend = false;
              }
              if (n > 2 * kSpin) break;
            }
          }
        }
      }
    }
  }
}

__global__ void probe_kernel() {}
int fits(int size) {
  cudaLaunchConfig_t cfg = {};
  cudaLaunchAttribute at;
  at.id = cudaLaunchAttributeClusterDimension;
  at.val.clusterDim.x = size; at.val.clusterDim.y = at.val.clusterDim.z = 1;
  cfg.gridDim = dim3(128); cfg.blockDim = dim3(384); cfg.dynamicSmemBytes = SMEM_BYTES; cfg.attrs = &at; cfg.numAttrs = 1;
  int n = 0;
  if (cudaOccupancyMaxActiveClusters(&n, probe_kernel, &cfg) != cudaSuccess) (void)cudaGetLastError();
  return n;
}

typedef CUresult (*EncFn)(CUtensorMap*, CUtensorMapDataType, cuuint32_t, void*, const cuuint64_t*, const cuuint64_t*, const cuuint32_t*,
                          const cuuint32_t*, CUtensorMapInterleave, CUtensorMapSwizzle, CUtensorMapL2promotion, CUtensorMapFloatOOBfill);

void make_map(EncFn enc, CUtensorMap* tm, const void* p, int cols, int rows, int bc, int br, CUtensorMapSwizzle sw) {
  cuuint64_t gd[2] = {(cuuint64_t)cols, (cuuint64_t)rows};
  cuuint64_t gs[1] = {(cuuint64_t)cols * 2};
  cuuint32_t bd[2] = {(cuuint32_t)bc, (cuuint32_t)br};
  cuuint32_t es[2] = {1, 1};
  enc(tm, CU_TENSOR_MAP_DATA_TYPE_BFLOAT16, 2, (void*)p, gd, gs, bd, es, CU_TENSOR_MAP_INTERLEAVE_NONE, sw,
      CU_TENSOR_MAP_L2_PROMOTION_L2_256B, CU_TENSOR_MAP_FLOAT_OOB_FILL_NONE);
}

}

extern "C" void kernel_launch(void* const* d_in, const int* in_sizes, int n_in, void* d_out, int out_size) {
  static EncFn enc = nullptr;
  static void* scratch = nullptr;
  static uint4* wd = nullptr;
  static decltype(&fused_kernel<true>) kern = nullptr;
  if (!enc) {
    cudaGetSymbolAddress(&scratch, g_scratch);
    scratch = (void*)(((uintptr_t)scratch + (1 << 21) - 1) & ~(uintptr_t)((1 << 21) - 1));
    wd = (uint4*)((char*)scratch + kWd);
    scratch = (char*)scratch + SOFF;
    cudaDriverEntryPointQueryResult qr;
    cudaGetDriverEntryPoint("cuTensorMapEncodeTiled", (void**)&enc, cudaEnableDefault, &qr);
    cudaFuncSetAttribute(probe_kernel, cudaFuncAttributeMaxDynamicSharedMemorySize, SMEM_BYTES);
    kern = fits(2) == 66 && fits(4) == 30 && fits(8) == 15 ? fused_kernel<true> : fused_kernel<false>;
    cudaFuncSetAttribute(kern, cudaFuncAttributeMaxDynamicSharedMemorySize, SMEM_BYTES);
  }
  Maps tm;
  Dz dz;
  for (int i = 0; i < 8; i++) dz.z[i] = 0x4000004000010000ull;
  make_map(enc, &tm.m[0], d_in[0], 448, 2048, 64, 64, CU_TENSOR_MAP_SWIZZLE_128B);
  make_map(enc, &tm.m[1], d_in[1], 1344, 448, 56, 56, CU_TENSOR_MAP_SWIZZLE_128B);
  make_map(enc, &tm.m[2], d_in[3], 448, 448, 56, 56, CU_TENSOR_MAP_SWIZZLE_128B);
  make_map(enc, &tm.m[3], d_in[5], 1792, 448, 56, 56, CU_TENSOR_MAP_SWIZZLE_128B);
  make_map(enc, &tm.m[4], d_in[6], 1792, 448, 56, 56, CU_TENSOR_MAP_SWIZZLE_128B);
  make_map(enc, &tm.m[5], wd, 512, 1792, 56, 56, CU_TENSOR_MAP_SWIZZLE_128B);
  kern<<<128, 384, SMEM_BYTES>>>((Scratch*)scratch, (const __nv_bfloat16*)d_in[2], (const __nv_bfloat16*)d_in[1], (const __nv_bfloat16*)d_in[7], wd, 0, tm,
                                 (const __nv_bfloat16*)d_in[5], (const __nv_bfloat16*)d_in[6], (const __nv_bfloat16*)d_in[3], (__nv_bfloat16*)d_out, dz);
}
```
